```python
import torch

def _softmax(x, axis=-1):
    return torch.softmax(x, dim=axis)

def _gelu(x):
    return torch.nn.functional.gelu(x, approximate='tanh')

def _silu(x):
    return torch.nn.functional.silu(x)

def _sigmoid(x):
    return torch.sigmoid(x)

def _layernorm(x, axis=-1, eps=1e-05):
    m = x.mean(dim=axis, keepdim=True)
    v = x.var(dim=axis, keepdim=True, unbiased=False)
    return (x - m) / torch.sqrt(v + eps)

def _scatter_add(tgt, idx, src, axis=0):
    return tgt.clone().index_add_(axis, idx, src)

def _segment_sum(src, seg, n):
    out = torch.zeros((n,) + src.shape[1:], dtype=src.dtype)
    return out.index_add_(0, seg, src)

def _pad(x, pw):
    flat = tuple((v for pair in reversed(pw) for v in pair))
    return torch.nn.functional.pad(x, flat)
kernel_name = 'adaLN_cond__sliding_block_cached__geglu_ffn__decode'

def setup_inputs():

    _w = lambda a: (lambda t: t.to(torch.bfloat16) if t.is_floating_point() else t)(torch.as_tensor(a))

    def _A_setup():
        B, Sq, D = (4, 1, 512)
        Hq, Hkv, Sk, Dh = (32, 8, 16384, 128)
        assert Hq % Hkv == 0, (Hq, Hkv)
        return {'x': _w((lambda *s: torch.randn(*s, dtype=torch.bfloat16) * 0.05)(B, Sq, D)), 'k_cache': _w((lambda *s: torch.randn(*s, dtype=torch.bfloat16) * 1.6)(B, Hkv, Sk, Dh)), 'v_cache': _w((lambda *s: torch.randn(*s, dtype=torch.bfloat16) * 1.6)(B, Hkv, Sk, Dh)), 'wq': _w((lambda *s: torch.randn(*s, dtype=torch.bfloat16) * 1.6)(D, Hq * Dh) * D ** (-0.5)), 'wo': _w((lambda *s: torch.randn(*s, dtype=torch.bfloat16) * 1.6)(Hq * Dh, D) * (Hq * Dh) ** (-0.5))}
    _A_in = _A_setup()

    def _B_setup():
        B, S, D, F = (4, 1, 512, 1792)
        return {'x': _w((lambda *s: torch.randn(*s, dtype=torch.bfloat16) * 0.05)(B, S, D)), 'w_gate': _w((lambda *s: torch.randn(*s, dtype=torch.bfloat16) * 0.05)(D, F)), 'w_up': _w((lambda *s: torch.randn(*s, dtype=torch.bfloat16) * 0.05)(D, F)), 'w_down': _w((lambda *s: torch.randn(*s, dtype=torch.bfloat16) * 0.05)(F, D))}
    _B_in = _B_setup()
    return {'A_x': _A_in['x'], 'A_k_cache': _A_in['k_cache'], 'A_v_cache': _A_in['v_cache'], 'A_wq': _A_in['wq'], 'A_wo': _A_in['wo'], 'B_x': _B_in['x'], 'B_w_gate': _B_in['w_gate'], 'B_w_up': _B_in['w_up'], 'B_w_down': _B_in['w_down'], 'c': _w((lambda *s: torch.randn(*s, dtype=torch.bfloat16) * 0.2)(4, 512) * 8.0), 'w_mod': _w((lambda *s: torch.randn(*s, dtype=torch.bfloat16) * 0.2)(512, 6 * 512) * 512 ** (-0.5) * 8.0)}

def reference(A_x, A_k_cache, A_v_cache, A_wq, A_wo, B_x, B_w_gate, B_w_up, B_w_down, c, w_mod):

    def _A_ref(x, k_cache, v_cache, wq, wo):
        B, Sq, D = x.shape
        Hq, Dh = (32, 128)
        Hkv, Sk = (k_cache.shape[1], k_cache.shape[2])
        W = min(4096, max(256, Sk // 4))
        rep = Hq // Hkv
        q = (lambda x, *d: x.permute(*d))((x @ wq).reshape(B, Sq, Hq, Dh), 0, 2, 1, 3)
        k = (lambda x, n, axis: torch.repeat_interleave(x, n, dim=axis))(k_cache[:, :, Sk - W:, :], rep, axis=1)
        v = (lambda x, n, axis: torch.repeat_interleave(x, n, dim=axis))(v_cache[:, :, Sk - W:, :], rep, axis=1)
        scores = torch.einsum('bhqd,bhkd->bhqk', q, k) * Dh ** (-0.5)
        p = _softmax(scores, axis=-1)
        o = torch.einsum('bhqk,bhkd->bhqd', p, v)
        return (lambda x, *d: x.permute(*d))(o, 0, 2, 1, 3).reshape(B, Sq, Hq * Dh) @ wo

    def _B_ref(x, w_gate, w_up, w_down):
        return _gelu(x @ w_gate) * (x @ w_up) @ w_down
    x = A_x
    mod = (_silu(c) @ w_mod).reshape(c.shape[0], 6, 1, -1)
    sa, ca, ga, sb, cb, gb = (mod[:, 0].clone(), mod[:, 1].clone(), mod[:, 2].clone(), mod[:, 3].clone(), mod[:, 4].clone(), mod[:, 5].clone())
    h = _layernorm(x, axis=-1) * (1 + ca) + sa
    x = x + ga * _A_ref(h, A_k_cache, A_v_cache, A_wq, A_wo)
    h = _layernorm(x, axis=-1) * (1 + cb) + sb
    x = x + gb * _B_ref(h, B_w_gate, B_w_up, B_w_down)
    return x
```

```cpp
#include <cuda_runtime.h>
#include <cuda_bf16.h>
#include <cuda.h>
#include <stdint.h>

typedef __nv_bfloat16 bf16;

constexpr int NB = 4, DM = 512, HQ = 32, HKV = 8, SK = 16384, DH = 128, WIN = 4096, FF = 1792;
constexpr int NCTA = 128;
constexpr int NFFN = 112;
constexpr int KEYS_PER_CTA = 1024;
constexpr int TILE_KEYS = 64;
constexpr int NTILE = KEYS_PER_CTA / TILE_KEYS;
constexpr int SLOT_BYTES = 16384;
#define NSLOT 12
#define INFLIGHT 12
#define P_WO 28
#define P_GU 30
#define P_DN 32
constexpr int NSEQ = 2 + 2 * NTILE + 5;
constexpr int NCONS = 256;
constexpr int NTHREADS = NCONS + 32;

__host__ __device__ constexpr int kv2pos(int kv) {
    return 2 + kv + (kv >= P_WO ? 2 : 0) + (kv >= P_GU ? 2 : 0) + (kv >= P_DN ? 1 : 0);
}
__host__ __device__ constexpr int posK(int i) { return kv2pos(i == 0 ? 0 : 2 * i - 1); }
__host__ __device__ constexpr int posV(int i) { return kv2pos(i == NTILE - 1 ? 2 * NTILE - 1 : 2 * i + 2); }
constexpr int POS_WO = 2 + P_WO;
constexpr int POS_GU = 2 + P_GU + 2;
constexpr int POS_DN = 2 + P_DN + 4;
static_assert(P_WO <= P_GU && P_GU <= P_DN && P_DN <= 32, "order");
static_assert(POS_WO >= NSEQ - NSLOT, "tail weights must never need to be recycled");

__device__ unsigned g_epoch;
__device__ __align__(128) unsigned g_llh[NCTA * 16];
__device__ __align__(128) unsigned g_llsc[NCTA * 32];
__device__ __align__(128) unsigned g_llq[NB * HQ * DH];
__device__ __align__(128) unsigned g_llo[NCTA * 16 * 32];
__device__ __align__(128) unsigned g_llml[HQ * 16 * 2];
__device__ __align__(128) unsigned g_ll2[NCTA * NCTA * 16];
__device__ __align__(128) unsigned g_ll3[NCTA * 16];
__device__ __align__(128) unsigned g_ll4[NCTA * NFFN * 16];
#define STAMP(i)
#define PSTAMP(i)

__device__ __forceinline__ uint32_t smem_u32(const void* p) { return (uint32_t)__cvta_generic_to_shared(p); }
__device__ __forceinline__ float bfr(float x) { return __bfloat162float(__float2bfloat16_rn(x)); }
__device__ __forceinline__ float bf_lo(uint32_t u) { return __uint_as_float(u << 16); }
__device__ __forceinline__ float bf_hi(uint32_t u) { return __uint_as_float(u & 0xffff0000u); }
__device__ __forceinline__ uint32_t pack_bf2(float lo, float hi) {
    uint32_t r; asm("cvt.rn.bf16x2.f32 %0, %1, %2;" : "=r"(r) : "f"(hi), "f"(lo)); return r;
}
__device__ __forceinline__ uint32_t bf_bits(float x) { return (uint32_t)__bfloat16_as_ushort(__float2bfloat16_rn(x)); }

__device__ __forceinline__ void mbar_init(uint32_t bar, uint32_t cnt) {
    asm volatile("mbarrier.init.shared::cta.b64 [%0], %1;" :: "r"(bar), "r"(cnt) : "memory");
}
__device__ __forceinline__ void mbar_expect_tx(uint32_t bar, uint32_t bytes) {
    asm volatile("mbarrier.arrive.expect_tx.shared::cta.b64 _, [%0], %1;" :: "r"(bar), "r"(bytes) : "memory");
}
__device__ __forceinline__ void mbar_arrive(uint32_t bar) {
    asm volatile("mbarrier.arrive.shared::cta.b64 _, [%0];" :: "r"(bar) : "memory");
}
__device__ __forceinline__ bool mbar_try(uint32_t bar, uint32_t parity) {
    uint32_t ok;
    asm volatile("{\n\t.reg .pred p;\n\tmbarrier.try_wait.parity.shared::cta.b64 p, [%1], %2;\n\tselp.u32 %0, 1, 0, p;\n\t}"
                 : "=r"(ok) : "r"(bar), "r"(parity) : "memory");
    return ok != 0;
}
constexpr int SPIN_LIMIT = 1 << 22;
__device__ __forceinline__ void mbar_wait(uint32_t bar, uint32_t parity) {
    for (int i = 0; i < SPIN_LIMIT; i++) if (mbar_try(bar, parity)) return;
}
__device__ __forceinline__ void tma2d(uint32_t dst, const CUtensorMap* tm, int c0, int c1, uint32_t bar) {
    asm volatile("cp.async.bulk.tensor.2d.shared::cluster.global.tile.mbarrier::complete_tx::bytes [%0], [%1, {%3, %4}], [%2];"
                 :: "r"(dst), "l"((uint64_t)tm), "r"(bar), "r"(c0), "r"(c1) : "memory");
}
__device__ __forceinline__ void tma3d(uint32_t dst, const CUtensorMap* tm, int c0, int c1, int c2, uint32_t bar) {
    asm volatile("cp.async.bulk.tensor.3d.shared::cluster.global.tile.mbarrier::complete_tx::bytes [%0], [%1, {%3, %4, %5}], [%2];"
                 :: "r"(dst), "l"((uint64_t)tm), "r"(bar), "r"(c0), "r"(c1), "r"(c2) : "memory");
}
__device__ __forceinline__ void tma3d_hint(uint32_t dst, const CUtensorMap* tm, int c0, int c1, int c2, uint32_t bar, uint64_t pol) {
    asm volatile("cp.async.bulk.tensor.3d.shared::cluster.global.tile.mbarrier::complete_tx::bytes.L2::cache_hint [%0], [%1, {%3, %4, %5}], [%2], %6;"
                 :: "r"(dst), "l"((uint64_t)tm), "r"(bar), "r"(c0), "r"(c1), "r"(c2), "l"(pol) : "memory");
}
__device__ __forceinline__ void ldsm4(uint32_t (&r)[4], uint32_t addr) {
    asm volatile("ldmatrix.sync.aligned.m8n8.x4.shared.b16 {%0,%1,%2,%3}, [%4];"
                 : "=r"(r[0]), "=r"(r[1]), "=r"(r[2]), "=r"(r[3]) : "r"(addr) : "memory");
}
__device__ __forceinline__ void ldsm4t(uint32_t (&r)[4], uint32_t addr) {
    asm volatile("ldmatrix.sync.aligned.m8n8.x4.trans.shared.b16 {%0,%1,%2,%3}, [%4];"
                 : "=r"(r[0]), "=r"(r[1]), "=r"(r[2]), "=r"(r[3]) : "r"(addr) : "memory");
}
__device__ __forceinline__ void mma16816(float (&c)[4], const uint32_t (&a)[4], uint32_t b0, uint32_t b1) {
    asm volatile("mma.sync.aligned.m16n8k16.row.col.f32.bf16.bf16.f32 {%0,%1,%2,%3}, {%4,%5,%6,%7}, {%8,%9}, {%0,%1,%2,%3};"
                 : "+f"(c[0]), "+f"(c[1]), "+f"(c[2]), "+f"(c[3])
                 : "r"(a[0]), "r"(a[1]), "r"(a[2]), "r"(a[3]), "r"(b0), "r"(b1));
}
__device__ __forceinline__ uint32_t movm_t(uint32_t a) {
    uint32_t d; asm volatile("movmatrix.sync.aligned.m8n8.trans.b16 %0, %1;" : "=r"(d) : "r"(a)); return d;
}
__device__ __forceinline__ void cons_sync() { asm volatile("bar.sync 1, 256;" ::: "memory"); }

__device__ __forceinline__ uint4 ld_rlx4(const unsigned* p) {
    uint4 v;
    asm volatile("ld.relaxed.gpu.global.v4.u32 {%0,%1,%2,%3}, [%4];" : "=r"(v.x), "=r"(v.y), "=r"(v.z), "=r"(v.w) : "l"(p) : "memory");
    return v;
}
__device__ __forceinline__ uint2 ld_rlx2(const unsigned* p) {
    uint2 v;
    asm volatile("ld.relaxed.gpu.global.v2.u32 {%0,%1}, [%2];" : "=r"(v.x), "=r"(v.y) : "l"(p) : "memory");
    return v;
}
__device__ __forceinline__ void st_rlx(unsigned* p, unsigned v) {
    asm volatile("st.relaxed.gpu.global.u32 [%0], %1;" :: "l"(p), "r"(v) : "memory");
}
__device__ __forceinline__ void st_rlx2(unsigned* p, unsigned a, unsigned b) {
    asm volatile("st.relaxed.gpu.global.v2.u32 [%0], {%1,%2};" :: "l"(p), "r"(a), "r"(b) : "memory");
}
__device__ __forceinline__ bool tag_ok(const uint4& v, unsigned tag, unsigned mask) {
    return (((v.x ^ tag) | (v.y ^ tag) | (v.z ^ tag) | (v.w ^ tag)) & mask) == 0;
}
__device__ __forceinline__ uint4 poll4(const unsigned* p, unsigned tag, unsigned mask) {
    uint4 v = ld_rlx4(p);
    for (int i = 0; i < SPIN_LIMIT && !tag_ok(v, tag, mask); i++) v = ld_rlx4(p);
    return v;
}
__device__ __forceinline__ void poll4x2(const unsigned* p0, const unsigned* p1, unsigned tag, unsigned mask, uint4& a, uint4& b) {
    a = ld_rlx4(p0); b = ld_rlx4(p1);
    for (int i = 0; i < SPIN_LIMIT; i++) {
        bool oa = tag_ok(a, tag, mask), ob = tag_ok(b, tag, mask);
        if (oa && ob) break;
        if (!oa) a = ld_rlx4(p0);
        if (!ob) b = ld_rlx4(p1);
    }
}
__device__ __forceinline__ unsigned tagf(float v, unsigned tag4) { return (__float_as_uint(v) & ~0xFu) | tag4; }
__device__ __forceinline__ float untagf(unsigned u) { return __uint_as_float(u & ~0xFu); }

__device__ __forceinline__ float warp_reduce32(float (&v)[32], int lane) {
#pragma unroll
    for (int s = 16; s >= 1; s >>= 1) {
        const bool up = (lane & s) != 0;
#pragma unroll
        for (int i = 0; i < s; i++) {
            float send = up ? v[i] : v[i + s];
            float keep = up ? v[i + s] : v[i];
            v[i] = keep + __shfl_xor_sync(0xffffffffu, send, s);
        }
    }
    return v[0];
}

constexpr int SM_RING = 0;
constexpr int SM_MISC = NSLOT * SLOT_BYTES;
constexpr int ACT_PITCH = 520;
constexpr int SM_OBUF  = SM_MISC;
constexpr int SM_ACT   = SM_OBUF + 16384;
constexpr int SM_QS    = SM_ACT + 4 * ACT_PITCH * 2;
constexpr int SM_RED   = SM_QS + 4 * 136 * 2;
constexpr int SM_ML    = SM_RED + 3 * 8 * 32 * 4;
constexpr int SM_ST    = SM_ML + 8 * 4 * 2 * 4;
constexpr int SM_BAR   = SM_ST + 64 * 4;
constexpr int SM_TOTAL = SM_BAR + 2 * NSLOT * 8 + 1024;
static_assert(SM_TOTAL <= 232448, "smem");

__global__ void __launch_bounds__(NTHREADS, 1)
fused_kernel(const __grid_constant__ CUtensorMap tmK, const __grid_constant__ CUtensorMap tmV,
             const __grid_constant__ CUtensorMap tmWq, const __grid_constant__ CUtensorMap tmWo,
             const __grid_constant__ CUtensorMap tmWg, const __grid_constant__ CUtensorMap tmWu,
             const __grid_constant__ CUtensorMap tmWd,
             const bf16* __restrict__ x, const bf16* __restrict__ cvec, const bf16* __restrict__ wmod,
             bf16* __restrict__ out)
{
    extern __shared__ uint8_t smem_raw[];
    uint8_t* smem = (uint8_t*)(((uintptr_t)smem_raw + 1023) & ~(uintptr_t)1023);
    const uint32_t sbase = smem_u32(smem);
    const int tid = threadIdx.x, warp = tid >> 5, lane = tid & 31;
    const int j = blockIdx.x;
    const int ab = j >> 5, ag = (j >> 2) & 7, as = j & 3;
    const uint32_t bar_full = sbase + SM_BAR, bar_empty = bar_full + NSLOT * 8;

    if (warp == 8) {
        if (lane == 0) {
            PSTAMP(16);
            for (int s = 0; s < NSLOT; s++) { mbar_init(bar_full + s * 8, 1); mbar_init(bar_empty + s * 8, 4); }
            asm volatile("fence.mbarrier_init.release.cluster;" ::: "memory");
            asm volatile("fence.proxy.async.shared::cta;" ::: "memory");
        }
        __syncwarp();
        asm volatile("bar.arrive 2, 288;" ::: "memory");
        if (lane == 0) {
            uint64_t pol;
            asm volatile("createpolicy.fractional.L2::evict_first.b64 %0, 1.0;" : "=l"(pol));
            const int row0 = (ab * HKV + ag) * SK + (SK - WIN) + as * KEYS_PER_CTA;
            int kv = 0;
            for (int pos = 0; pos < NSEQ; pos++) {
                const int slot = pos % NSLOT, use = pos / NSLOT;
                const uint32_t dst = sbase + SM_RING + slot * SLOT_BYTES, fb = bar_full + slot * 8;
                const bool ffn_tile = (pos == POS_GU || pos == POS_GU + 1 || pos == POS_DN);
                if (ffn_tile && j >= NFFN) continue;
                if (pos >= INFLIGHT && INFLIGHT < NSLOT) {
                    const int p2 = pos - INFLIGHT;
                    const bool skip = (p2 == POS_GU || p2 == POS_GU + 1 || p2 == POS_DN) && j >= NFFN;
                    if (!skip) mbar_wait(bar_full + (p2 % NSLOT) * 8, (p2 / NSLOT) & 1);
                }
                if (use > 0) mbar_wait(bar_empty + slot * 8, (use - 1) & 1);
                mbar_expect_tx(fb, SLOT_BYTES);
                if (pos < 2) {
                    tma2d(dst, &tmWq, 32 * j, 256 * pos, fb);
                } else if (pos == POS_WO || pos == POS_WO + 1) {
                    tma3d(dst, &tmWo, 0, 32 * j, 4 * (pos - POS_WO), fb);
                } else if (pos == POS_GU || pos == POS_GU + 1) {
                    const CUtensorMap* tm = (pos == POS_GU) ? &tmWg : &tmWu;
                    tma2d(dst, tm, 16 * j, 0, fb);
                    tma2d(dst + 8192, tm, 16 * j, 256, fb);
                } else if (pos == POS_DN) {
                    tma3d(dst, &tmWd, 0, 16 * j, 0, fb);
                } else {
                    const bool isK = (kv == 0) || ((kv & 1) && kv < 2 * NTILE - 1);
                    const int ti = isK ? ((kv + 1) >> 1) : (kv == 2 * NTILE - 1 ? NTILE - 1 : (kv >> 1) - 1);
                    tma3d_hint(dst, isK ? &tmK : &tmV, 0, row0 + ti * TILE_KEYS, 0, fb, pol);
                    kv++;
                }
            }
            PSTAMP(17);
        }
        return;
    }

    STAMP(0);
    float* obuf = (float*)(smem + SM_OBUF);
    bf16* act_s = (bf16*)(smem + SM_ACT);
    bf16* qs = (bf16*)(smem + SM_QS);
    float* red = (float*)(smem + SM_RED);
    float* mls = (float*)(smem + SM_ML);
    float* st = (float*)(smem + SM_ST);
    const int g = lane >> 2, t = lane & 3;

    unsigned epoch;
    asm volatile("ld.relaxed.gpu.global.u32 %0, [%1];" : "=r"(epoch) : "l"(&g_epoch) : "memory");
    uint2 wm[6][2];
#pragma unroll
    for (int ch = 0; ch < 6; ch++)
#pragma unroll
        for (int i = 0; i < 2; i++) {
            const bf16* p = wmod + (size_t)(tid + 256 * i) * (6 * DM) + ch * DM + 4 * j;
            asm volatile("ld.global.nc.L2::128B.v2.u32 {%0,%1}, [%2];" : "=r"(wm[ch][i].x), "=r"(wm[ch][i].y) : "l"(p));
        }
    float sc[2][4];
#pragma unroll
    for (int i = 0; i < 2; i++)
#pragma unroll
        for (int b = 0; b < 4; b++) sc[i][b] = __bfloat162float(cvec[b * DM + tid + 256 * i]);
    float xown = 0.f;
    if (tid < 16) xown = __bfloat162float(x[(tid >> 2) * DM + 4 * j + (tid & 3)]);
    if (warp < 4) {
        const uint4* xp = (const uint4*)(x + warp * DM);
        uint4 u0 = __ldg(xp + lane), u1 = __ldg(xp + 32 + lane);
        uint32_t w[8] = {u0.x, u0.y, u0.z, u0.w, u1.x, u1.y, u1.z, u1.w};
        float s = 0.f;
#pragma unroll
        for (int i = 0; i < 8; i++) s += bf_lo(w[i]) + bf_hi(w[i]);
#pragma unroll
        for (int o = 16; o; o >>= 1) s += __shfl_xor_sync(0xffffffffu, s, o);
        const float mean = s * (1.f / DM);
        float q = 0.f;
#pragma unroll
        for (int i = 0; i < 8; i++) { float a = bf_lo(w[i]) - mean, b2 = bf_hi(w[i]) - mean; q += a * a + b2 * b2; }
#pragma unroll
        for (int o = 16; o; o >>= 1) q += __shfl_xor_sync(0xffffffffu, q, o);
        if (lane == 0) {
            st[warp] = bfr(mean);
            st[4 + warp] = bfr(sqrtf(bfr(bfr(q * (1.f / DM)) + 1e-5f)));
        }
    }
#pragma unroll
    for (int i = 0; i < 2; i++)
#pragma unroll
        for (int b = 0; b < 4; b++) { float v = sc[i][b]; sc[i][b] = bfr(v / (1.f + __expf(-v))); }
    const unsigned tag16 = (epoch + 1) & 0xffffu, tag4 = (epoch + 1) & 0xfu;

    auto mod_pair = [&](int c0, int c1, int slot) {
        float v[32];
#pragma unroll
        for (int h = 0; h < 2; h++) {
            const int ch = h ? c1 : c0;
#pragma unroll
            for (int b = 0; b < 4; b++) {
                v[h * 16 + b * 4 + 0] = sc[0][b] * bf_lo(wm[ch][0].x) + sc[1][b] * bf_lo(wm[ch][1].x);
                v[h * 16 + b * 4 + 1] = sc[0][b] * bf_hi(wm[ch][0].x) + sc[1][b] * bf_hi(wm[ch][1].x);
                v[h * 16 + b * 4 + 2] = sc[0][b] * bf_lo(wm[ch][0].y) + sc[1][b] * bf_lo(wm[ch][1].y);
                v[h * 16 + b * 4 + 3] = sc[0][b] * bf_hi(wm[ch][0].y) + sc[1][b] * bf_hi(wm[ch][1].y);
            }
        }
        float r = warp_reduce32(v, lane);
        red[slot * 256 + warp * 32 + lane] = r;
    };
    mod_pair(0, 1, 0);
    cons_sync();
    if (tid < 16) {
        float sa = 0.f, ca = 0.f;
#pragma unroll
        for (int w = 0; w < 8; w++) { sa += red[w * 32 + tid]; ca += red[w * 32 + 16 + tid]; }
        sa = bfr(sa); ca = bfr(ca);
        const int b = tid >> 2;
        float hn = bfr(bfr(xown - st[b]) / st[4 + b]);
        float hv = bfr(hn * bfr(1.f + ca)) + sa;
        st_rlx(&g_llh[j * 16 + tid], (bf_bits(hv) << 16) | tag16);
    }
    STAMP(1);
    mod_pair(3, 4, 1);
    mod_pair(2, 5, 2);
    cons_sync();
    if (tid < 32) {
        float a = 0.f;
#pragma unroll
        for (int w = 0; w < 8; w++) a += red[256 + w * 32 + tid];
        a = bfr(a);
        if (tid >= 16) a = bfr(1.f + a);
        st_rlx(&g_llsc[j * 32 + tid], (bf_bits(a) << 16) | tag16);
    } else if (tid < 64) {
        float a = 0.f;
#pragma unroll
        for (int w = 0; w < 8; w++) a += red[512 + w * 32 + (tid - 32)];
        st[16 + (tid - 32)] = bfr(a);
    }

    {
        uint4 a, b;
        poll4x2(&g_llh[tid * 4], &g_llh[(tid + 256) * 4], tag16, 0xffffu, a, b);
        const int bb = tid & 3, jj = tid >> 2;
        *(uint2*)(act_s + bb * ACT_PITCH + 4 * jj) = make_uint2((a.x >> 16) | (a.y & 0xffff0000u), (a.z >> 16) | (a.w & 0xffff0000u));
        *(uint2*)(act_s + bb * ACT_PITCH + 4 * (jj + 64)) = make_uint2((b.x >> 16) | (b.y & 0xffff0000u), (b.z >> 16) | (b.w & 0xffff0000u));
    }
    asm volatile("bar.sync 2, 288;" ::: "memory");
    STAMP(2);

    const int mi = lane >> 3, lr = lane & 7;
    {
        mbar_wait(bar_full + (warp >> 2) * 8, 0);
        float acc[2][4] = {};
        const uint32_t base = sbase + SM_RING + (warp >> 2) * SLOT_BYTES;
#pragma unroll
        for (int ks = 0; ks < 4; ks++) {
            const int k0 = warp * 64 + ks * 16;
            uint32_t b0 = 0, b1 = 0;
            if (g < 4) {
                b0 = *(const uint32_t*)(act_s + g * ACT_PITCH + k0 + 2 * t);
                b1 = *(const uint32_t*)(act_s + g * ACT_PITCH + k0 + 2 * t + 8);
            }
            const int row = (warp & 3) * 64 + ks * 16 + lr + (mi >> 1) * 8;
#pragma unroll
            for (int mt = 0; mt < 2; mt++) {
                uint32_t a[4];
                ldsm4t(a, base + row * 64 + (((2 * mt + (mi & 1)) ^ ((row >> 1) & 3)) << 4));
                mma16816(acc[mt], a, b0, b1);
            }
        }
        if (t < 2) {
#pragma unroll
            for (int mt = 0; mt < 2; mt++) {
                obuf[warp * 128 + (2 * t) * 32 + mt * 16 + g] = acc[mt][0];
                obuf[warp * 128 + (2 * t + 1) * 32 + mt * 16 + g] = acc[mt][1];
                obuf[warp * 128 + (2 * t) * 32 + mt * 16 + g + 8] = acc[mt][2];
                obuf[warp * 128 + (2 * t + 1) * 32 + mt * 16 + g + 8] = acc[mt][3];
            }
        }
        cons_sync();
        if (tid < 128) {
            float s = 0.f;
#pragma unroll
            for (int w = 0; w < 8; w++) s += obuf[w * 128 + tid];
            st_rlx(&g_llq[(tid >> 5) * (HQ * DH) + 32 * j + (tid & 31)], (bf_bits(s) << 16) | tag16);
            if (lane == 0) { mbar_arrive(bar_empty); mbar_arrive(bar_empty + 8); }
        }
    }
    STAMP(3);
    uint32_t sbp[2][2], cbp[2][2];
    {
        const int bb = tid & 3;
#pragma unroll
        for (int i = 0; i < 2; i++) {
            const int jj = (tid >> 2) + 64 * i;
            uint4 a, b;
            poll4x2(&g_llsc[jj * 32 + bb * 4], &g_llsc[jj * 32 + 16 + bb * 4], tag16, 0xffffu, a, b);
            sbp[i][0] = (a.x >> 16) | (a.y & 0xffff0000u); sbp[i][1] = (a.z >> 16) | (a.w & 0xffff0000u);
            cbp[i][0] = (b.x >> 16) | (b.y & 0xffff0000u); cbp[i][1] = (b.z >> 16) | (b.w & 0xffff0000u);
        }
    }
    if (tid < 128) {
        uint4 a = poll4(&g_llq[ab * (HQ * DH) + ag * 512 + tid * 4], tag16, 0xffffu);
        *(uint2*)(qs + (tid >> 5) * 136 + (tid & 31) * 4) = make_uint2((a.x >> 16) | (a.y & 0xffff0000u), (a.z >> 16) | (a.w & 0xffff0000u));
    }
    cons_sync();
    uint32_t qf[8][2];
#pragma unroll
    for (int ks = 0; ks < 8; ks++) {
        qf[ks][0] = 0; qf[ks][1] = 0;
        if (g < 4) {
            qf[ks][0] = *(const uint32_t*)(qs + g * 136 + ks * 16 + 2 * t);
            qf[ks][1] = *(const uint32_t*)(qs + g * 136 + ks * 16 + 2 * t + 8);
        }
    }
    STAMP(4);

    float o[8][4];
#pragma unroll
    for (int i = 0; i < 8; i++) { o[i][0] = o[i][1] = o[i][2] = o[i][3] = 0.f; }
    float m0 = -INFINITY, m1 = -INFINITY, l0 = 0.f, l1 = 0.f;
    {
        const int w4 = warp & 3, grp = warp >> 2;
        const int keyK = w4 * 16 + lr + (mi & 1) * 8, chK = mi >> 1;
        const int keyV = w4 * 16 + lr + (mi >> 1) * 8, chV = mi & 1;
        const uint32_t offK = keyK * 128, offV = keyV * 128;
        const float LOG2E = 1.4426950408889634f;
#pragma unroll 1
        for (int it = 0; it < NTILE / 2; it++) {
            const int ti = 2 * it + grp;
            const int pk = posK(ti), pv = posV(ti);
            const int sk = pk % NSLOT, sv = pv % NSLOT;
            mbar_wait(bar_full + sk * 8, (pk / NSLOT) & 1);
            float s0[4] = {0.f, 0.f, 0.f, 0.f}, s1[4] = {0.f, 0.f, 0.f, 0.f};
            const uint32_t kb = sbase + SM_RING + sk * SLOT_BYTES + offK;
#pragma unroll
            for (int ks = 0; ks < 4; ks++) {
                uint32_t a[4], a2[4];
                const uint32_t sw = (uint32_t)(((2 * ks + chK) ^ lr) << 4);
                ldsm4(a, kb + sw);
                ldsm4(a2, kb + 8192 + sw);
                mma16816(s0, a, qf[ks][0], qf[ks][1]);
                mma16816(s1, a2, qf[4 + ks][0], qf[4 + ks][1]);
            }
            __syncwarp();
            if (lane == 0) mbar_arrive(bar_empty + sk * 8);
            float sv4[4];
#pragma unroll
            for (int i = 0; i < 4; i++) sv4[i] = bfr(bfr(s0[i] + s1[i]) * 0.08838834764831845f);
            float x0 = fmaxf(sv4[0], sv4[2]), x1 = fmaxf(sv4[1], sv4[3]);
#pragma unroll
            for (int off = 4; off < 32; off <<= 1) {
                x0 = fmaxf(x0, __shfl_xor_sync(0xffffffffu, x0, off));
                x1 = fmaxf(x1, __shfl_xor_sync(0xffffffffu, x1, off));
            }
            const float n0 = fmaxf(m0, x0), n1 = fmaxf(m1, x1);
            if (__any_sync(0xffffffffu, n0 > m0 || n1 > m1)) {
                const float f0 = exp2f((m0 - n0) * LOG2E), f1 = exp2f((m1 - n1) * LOG2E);
                l0 *= f0; l1 *= f1;
#pragma unroll
                for (int i = 0; i < 8; i++) { o[i][0] *= f0; o[i][1] *= f1; o[i][2] *= f0; o[i][3] *= f1; }
                m0 = n0; m1 = n1;
            }
            const float p0 = exp2f((sv4[0] - m0) * LOG2E), p1 = exp2f((sv4[1] - m1) * LOG2E);
            const float p2 = exp2f((sv4[2] - m0) * LOG2E), p3 = exp2f((sv4[3] - m1) * LOG2E);
            l0 += p0 + p2; l1 += p1 + p3;
            const uint32_t pb0 = movm_t(pack_bf2(p0, p1)), pb1 = movm_t(pack_bf2(p2, p3));
            mbar_wait(bar_full + sv * 8, (pv / NSLOT) & 1);
            const uint32_t vb = sbase + SM_RING + sv * SLOT_BYTES + offV;
#pragma unroll
            for (int mt = 0; mt < 8; mt++) {
                uint32_t a[4];
                ldsm4t(a, vb + (mt >> 2) * 8192 + (uint32_t)(((2 * (mt & 3) + chV) ^ lr) << 4));
                mma16816(o[mt], a, pb0, pb1);
            }
            __syncwarp();
            if (lane == 0) mbar_arrive(bar_empty + sv * 8);
        }
    }
    STAMP(5);
    {
#pragma unroll
        for (int off = 4; off < 32; off <<= 1) {
            l0 += __shfl_xor_sync(0xffffffffu, l0, off);
            l1 += __shfl_xor_sync(0xffffffffu, l1, off);
        }
        if (t < 2) {
            if (g == 0) {
                mls[(warp * 4 + 2 * t) * 2] = m0; mls[(warp * 4 + 2 * t) * 2 + 1] = l0;
                mls[(warp * 4 + 2 * t + 1) * 2] = m1; mls[(warp * 4 + 2 * t + 1) * 2 + 1] = l1;
            }
            float* ob = obuf + warp * 512;
#pragma unroll
            for (int mt = 0; mt < 8; mt++) {
                const int d = mt * 16 + g;
                ob[(2 * t) * 128 + ((d + 16 * t) & 127)] = o[mt][0];
                ob[(2 * t + 1) * 128 + ((d + 16 * t + 8) & 127)] = o[mt][1];
                ob[(2 * t) * 128 + ((d + 8 + 16 * t) & 127)] = o[mt][2];
                ob[(2 * t + 1) * 128 + ((d + 8 + 16 * t + 8) & 127)] = o[mt][3];
            }
        }
        cons_sync();
        const int hd = tid >> 6, d = (tid & 63) * 2;
        float mw[8], M = -INFINITY;
#pragma unroll
        for (int w = 0; w < 8; w++) { mw[w] = mls[(w * 4 + hd) * 2]; M = fmaxf(M, mw[w]); }
        float a0 = 0.f, a1 = 0.f, L = 0.f;
        const int dd = (d + 8 * hd) & 127;
#pragma unroll
        for (int w = 0; w < 8; w++) {
            const float f = exp2f((mw[w] - M) * 1.4426950408889634f);
            const float2 v = *(const float2*)(obuf + w * 512 + hd * 128 + dd);
            a0 += f * v.x; a1 += f * v.y;
            L += f * mls[(w * 4 + hd) * 2 + 1];
        }
        const int head = ag * 4 + hd, cons = head * 4 + (d >> 5);
        st_rlx2(&g_llo[((cons * 4 + ab) * 4 + as) * 32 + (d & 31)], tagf(a0, tag4), tagf(a1, tag4));
        if ((tid & 63) == 0) st_rlx2(&g_llml[((head * 4 + ab) * 4 + as) * 2], tagf(M, tag4), tagf(L, tag4));
    }
    STAMP(6);
    {
        if (tid < 128) {
            const int b = tid >> 5, s = (tid >> 3) & 3;
            const unsigned* mlp = &g_llml[((j >> 2) * 4 + b) * 8];
            uint4 mlA, mlB;
            uint4 ov = ld_rlx4(&g_llo[j * 512 + tid * 4]);
            poll4x2(mlp, mlp + 4, tag4, 0xfu, mlA, mlB);
            for (int i = 0; i < SPIN_LIMIT && !tag_ok(ov, tag4, 0xfu); i++) ov = ld_rlx4(&g_llo[j * 512 + tid * 4]);
            const float ms0 = untagf(mlA.x), ms1 = untagf(mlA.z), ms2 = untagf(mlB.x), ms3 = untagf(mlB.z);
            const float M = fmaxf(fmaxf(ms0, ms1), fmaxf(ms2, ms3));
            const float e0 = exp2f((ms0 - M) * 1.4426950408889634f), e1 = exp2f((ms1 - M) * 1.4426950408889634f);
            const float e2 = exp2f((ms2 - M) * 1.4426950408889634f), e3 = exp2f((ms3 - M) * 1.4426950408889634f);
            const float L = e0 * untagf(mlA.y) + e1 * untagf(mlA.w) + e2 * untagf(mlB.y) + e3 * untagf(mlB.w);
            const float f = (s == 0 ? e0 : s == 1 ? e1 : s == 2 ? e2 : e3) / L;
            float v0 = f * untagf(ov.x), v1 = f * untagf(ov.y), v2 = f * untagf(ov.z), v3 = f * untagf(ov.w);
#pragma unroll
            for (int off = 8; off < 32; off <<= 1) {
                v0 += __shfl_xor_sync(0xffffffffu, v0, off); v1 += __shfl_xor_sync(0xffffffffu, v1, off);
                v2 += __shfl_xor_sync(0xffffffffu, v2, off); v3 += __shfl_xor_sync(0xffffffffu, v3, off);
            }
            if (lane < 8) *(uint2*)(qs + b * 136 + lane * 4) = make_uint2(pack_bf2(v0, v1), pack_bf2(v2, v3));
        }
        mbar_wait(bar_full + ((POS_WO + (warp >> 2)) % NSLOT) * 8, ((POS_WO + (warp >> 2)) / NSLOT) & 1);
        cons_sync();
        STAMP(7);
        const uint32_t base = sbase + SM_RING + ((POS_WO + (warp >> 2)) % NSLOT) * SLOT_BYTES + (warp & 3) * 4096;
        float acc[4][4] = {};
#pragma unroll
        for (int ks = 0; ks < 2; ks++) {
            uint32_t b0 = 0, b1 = 0;
            if (g < 4) {
                b0 = *(const uint32_t*)(qs + g * 136 + ks * 16 + 2 * t);
                b1 = *(const uint32_t*)(qs + g * 136 + ks * 16 + 2 * t + 8);
            }
            const int row = ks * 16 + lr + (mi >> 1) * 8;
#pragma unroll
            for (int mt = 0; mt < 4; mt++) {
                uint32_t a[4];
                ldsm4t(a, base + row * 128 + (((2 * mt + (mi & 1)) ^ lr) << 4));
                mma16816(acc[mt], a, b0, b1);
            }
        }
        if (t < 2) {
#pragma unroll
            for (int mt = 0; mt < 4; mt++) {
                const int c0 = warp * 64 + mt * 16 + g, c1 = c0 + 8;
                st_rlx2(&g_ll2[((c0 >> 2) * NCTA + j) * 16 + (c0 & 3) * 4 + 2 * t], tagf(acc[mt][0], tag4), tagf(acc[mt][1], tag4));
                st_rlx2(&g_ll2[((c1 >> 2) * NCTA + j) * 16 + (c1 & 3) * 4 + 2 * t], tagf(acc[mt][2], tag4), tagf(acc[mt][3], tag4));
            }
        }
    }
    STAMP(8);
    {
        uint4 a, b;
        poll4x2(&g_ll2[j * (NCTA * 16) + tid * 4], &g_ll2[j * (NCTA * 16) + 1024 + tid * 4], tag4, 0xfu, a, b);
        float v0 = untagf(a.x) + untagf(b.x), v1 = untagf(a.y) + untagf(b.y), v2 = untagf(a.z) + untagf(b.z), v3 = untagf(a.w) + untagf(b.w);
#pragma unroll
        for (int off = 4; off < 32; off <<= 1) {
            v0 += __shfl_xor_sync(0xffffffffu, v0, off); v1 += __shfl_xor_sync(0xffffffffu, v1, off);
            v2 += __shfl_xor_sync(0xffffffffu, v2, off); v3 += __shfl_xor_sync(0xffffffffu, v3, off);
        }
        if (lane < 4) *(float4*)(red + warp * 16 + lane * 4) = make_float4(v0, v1, v2, v3);
        cons_sync();
        if (tid < 16) {
            const int bb = tid >> 2, cc = tid & 3;
            float s = 0.f;
#pragma unroll
            for (int w = 0; w < 8; w++) s += red[w * 16 + cc * 4 + bb];
            const float x1 = bfr(xown + bfr(st[16 + tid] * bfr(s)));
            xown = x1;
            st_rlx(&g_ll3[j * 16 + tid], (bf_bits(x1) << 16) | tag16);
        }
    }
    STAMP(9);
    if (j < NFFN) {
        uint4 a, b;
        poll4x2(&g_ll3[tid * 4], &g_ll3[(tid + 256) * 4], tag16, 0xffffu, a, b);
        float xv[8] = {bf_hi(a.x), bf_hi(a.y), bf_hi(a.z), bf_hi(a.w), bf_hi(b.x), bf_hi(b.y), bf_hi(b.z), bf_hi(b.w)};
        float mean = 0.f;
#pragma unroll
        for (int i = 0; i < 8; i++) mean += xv[i];
        mean *= 0.125f;
        float m2 = 0.f;
#pragma unroll
        for (int i = 0; i < 8; i++) m2 += (xv[i] - mean) * (xv[i] - mean);
        float n = 8.f;
#pragma unroll
        for (int off = 4; off < 32; off <<= 1) {
            const float om = __shfl_xor_sync(0xffffffffu, mean, off), o2 = __shfl_xor_sync(0xffffffffu, m2, off);
            const float dlt = om - mean;
            m2 = m2 + o2 + dlt * dlt * (n * 0.5f);
            mean = 0.5f * (mean + om);
            n *= 2.f;
        }
        if (lane < 4) { red[256 + (warp * 4 + lane) * 2] = mean; red[256 + (warp * 4 + lane) * 2 + 1] = m2; }
        cons_sync();
        const int bb = tid & 3;
        float mu = 0.f;
#pragma unroll
        for (int w = 0; w < 8; w++) mu += red[256 + (w * 4 + bb) * 2];
        mu *= 0.125f;
        float M2 = 0.f;
#pragma unroll
        for (int w = 0; w < 8; w++) { const float dm = red[256 + (w * 4 + bb) * 2] - mu; M2 += red[256 + (w * 4 + bb) * 2 + 1] + 64.f * dm * dm; }
        const float mub = bfr(mu), sd = bfr(sqrtf(bfr(bfr(M2 * (1.f / DM)) + 1e-5f)));
#pragma unroll
        for (int i = 0; i < 2; i++) {
            float hv[4];
#pragma unroll
            for (int c = 0; c < 4; c++) {
                const uint32_t sw = sbp[i][c >> 1], cw = cbp[i][c >> 1];
                const float sbv = (c & 1) ? bf_hi(sw) : bf_lo(sw), cbv = (c & 1) ? bf_hi(cw) : bf_lo(cw);
                hv[c] = bfr(bfr(bfr(xv[i * 4 + c] - mub) / sd) * cbv) + sbv;
            }
            *(uint2*)(act_s + bb * ACT_PITCH + 4 * ((tid >> 2) + 64 * i)) = make_uint2(pack_bf2(hv[0], hv[1]), pack_bf2(hv[2], hv[3]));
        }
        mbar_wait(bar_full + (POS_GU % NSLOT) * 8, (POS_GU / NSLOT) & 1);
        mbar_wait(bar_full + ((POS_GU + 1) % NSLOT) * 8, ((POS_GU + 1) / NSLOT) & 1);
        cons_sync();
        STAMP(10);
        {
            float acc[2][4] = {};
#pragma unroll
            for (int ks = 0; ks < 4; ks++) {
                const int k0 = warp * 64 + ks * 16;
                uint32_t b0 = 0, b1 = 0;
                if (g < 4) {
                    b0 = *(const uint32_t*)(act_s + g * ACT_PITCH + k0 + 2 * t);
                    b1 = *(const uint32_t*)(act_s + g * ACT_PITCH + k0 + 2 * t + 8);
                }
                const int row = k0 + lr + (mi >> 1) * 8;
                const uint32_t off = row * 32 + (((mi & 1) ^ ((row >> 2) & 1)) << 4);
#pragma unroll
                for (int mt = 0; mt < 2; mt++) {
                    uint32_t af[4];
                    ldsm4t(af, sbase + SM_RING + ((POS_GU + mt) % NSLOT) * SLOT_BYTES + off);
                    mma16816(acc[mt], af, b0, b1);
                }
            }
            if (t < 2) {
#pragma unroll
                for (int mt = 0; mt < 2; mt++) {
                    obuf[warp * 128 + (2 * t) * 32 + mt * 16 + g] = acc[mt][0];
                    obuf[warp * 128 + (2 * t + 1) * 32 + mt * 16 + g] = acc[mt][1];
                    obuf[warp * 128 + (2 * t) * 32 + mt * 16 + g + 8] = acc[mt][2];
                    obuf[warp * 128 + (2 * t + 1) * 32 + mt * 16 + g + 8] = acc[mt][3];
                }
            }
            cons_sync();
            if (tid < 64) {
                const int b2 = tid >> 4, cc = tid & 15;
                float gs = 0.f, us = 0.f;
#pragma unroll
                for (int w = 0; w < 8; w++) { gs += obuf[w * 128 + b2 * 32 + cc]; us += obuf[w * 128 + b2 * 32 + 16 + cc]; }
                gs = bfr(gs); us = bfr(us);
                const float inner = 0.7978845608028654f * (gs + 0.044715f * gs * gs * gs);
                const float ge = bfr(0.5f * gs * (1.f + tanhf(inner)));
                qs[b2 * 136 + cc] = __float2bfloat16_rn(ge * us);
            }
            mbar_wait(bar_full + (POS_DN % NSLOT) * 8, (POS_DN / NSLOT) & 1);
            cons_sync();
        }
        STAMP(11);
        {
            uint32_t b0 = 0, b1 = 0;
            if (g < 4) {
                b0 = *(const uint32_t*)(qs + g * 136 + 2 * t);
                b1 = *(const uint32_t*)(qs + g * 136 + 2 * t + 8);
            }
            const int row = lr + (mi >> 1) * 8;
            const uint32_t base = sbase + SM_RING + (POS_DN % NSLOT) * SLOT_BYTES + warp * 2048 + row * 128;
#pragma unroll
            for (int mt = 0; mt < 4; mt++) {
                uint32_t af[4];
                float acc[4] = {0.f, 0.f, 0.f, 0.f};
                ldsm4t(af, base + (((2 * mt + (mi & 1)) ^ lr) << 4));
                mma16816(acc, af, b0, b1);
                if (t < 2) {
                    const int c0 = warp * 64 + mt * 16 + g, c1 = c0 + 8;
                    st_rlx2(&g_ll4[((c0 >> 2) * NFFN + j) * 16 + (c0 & 3) * 4 + 2 * t], tagf(acc[0], tag4), tagf(acc[1], tag4));
                    st_rlx2(&g_ll4[((c1 >> 2) * NFFN + j) * 16 + (c1 & 3) * 4 + 2 * t], tagf(acc[2], tag4), tagf(acc[3], tag4));
                }
            }
        }
    }
    STAMP(12);
    {
        uint4 a, b = make_uint4(0, 0, 0, 0);
        if (tid < 192) poll4x2(&g_ll4[j * (NFFN * 16) + tid * 4], &g_ll4[j * (NFFN * 16) + 1024 + tid * 4], tag4, 0xfu, a, b);
        else a = poll4(&g_ll4[j * (NFFN * 16) + tid * 4], tag4, 0xfu);
        float v0 = untagf(a.x) + untagf(b.x), v1 = untagf(a.y) + untagf(b.y), v2 = untagf(a.z) + untagf(b.z), v3 = untagf(a.w) + untagf(b.w);
#pragma unroll
        for (int off = 4; off < 32; off <<= 1) {
            v0 += __shfl_xor_sync(0xffffffffu, v0, off); v1 += __shfl_xor_sync(0xffffffffu, v1, off);
            v2 += __shfl_xor_sync(0xffffffffu, v2, off); v3 += __shfl_xor_sync(0xffffffffu, v3, off);
        }
        if (lane < 4) *(float4*)(red + 512 + warp * 16 + lane * 4) = make_float4(v0, v1, v2, v3);
        cons_sync();
        if (tid < 16) {
            const int bb = tid >> 2, cc = tid & 3;
            float s = 0.f;
#pragma unroll
            for (int w = 0; w < 8; w++) s += red[512 + w * 16 + cc * 4 + bb];
            out[bb * DM + 4 * j + cc] = __float2bfloat16_rn(xown + bfr(st[32 + tid] * bfr(s)));
        }
        if (j == 0 && tid == 0) st_rlx(&g_epoch, epoch + 1);
    }
    STAMP(13);
}

typedef CUresult (*EncodeFn)(CUtensorMap*, CUtensorMapDataType, cuuint32_t, void*, const cuuint64_t*, const cuuint64_t*,
                             const cuuint32_t*, const cuuint32_t*, CUtensorMapInterleave, CUtensorMapSwizzle,
                             CUtensorMapL2promotion, CUtensorMapFloatOOBfill);

static void make_map(EncodeFn fn, CUtensorMap* m, void* ptr, int rank, const cuuint64_t* dims, const cuuint64_t* strides,
                     const cuuint32_t* box, CUtensorMapSwizzle sw, CUtensorMapL2promotion promo) {
    cuuint32_t es[3] = {1, 1, 1};
    fn(m, CU_TENSOR_MAP_DATA_TYPE_BFLOAT16, rank, ptr, dims, strides, box, es, CU_TENSOR_MAP_INTERLEAVE_NONE, sw, promo,
       CU_TENSOR_MAP_FLOAT_OOB_FILL_NONE);
}

extern "C" void kernel_launch(void* const* d_in, const int* in_sizes, int n_in, void* d_out, int out_size) {
    static EncodeFn fn = nullptr;
    if (!fn) {
        void* p = nullptr;
        cudaDriverEntryPointQueryResult qr;
        cudaGetDriverEntryPoint("cuTensorMapEncodeTiled", &p, cudaEnableDefault, &qr);
        fn = (EncodeFn)p;
        cudaFuncSetAttribute(fused_kernel, cudaFuncAttributeMaxDynamicSharedMemorySize, SM_TOTAL);
    }
    CUtensorMap tmK, tmV, tmWq, tmWo, tmWg, tmWu, tmWd;
    {
        cuuint64_t dims[3] = {64, (cuuint64_t)NB * HKV * SK, 2};
        cuuint64_t str[2] = {256, 128};
        cuuint32_t box[3] = {64, TILE_KEYS, 2};
        make_map(fn, &tmK, d_in[1], 3, dims, str, box, CU_TENSOR_MAP_SWIZZLE_128B, CU_TENSOR_MAP_L2_PROMOTION_L2_256B);
        make_map(fn, &tmV, d_in[2], 3, dims, str, box, CU_TENSOR_MAP_SWIZZLE_128B, CU_TENSOR_MAP_L2_PROMOTION_L2_256B);
    }
    {
        cuuint64_t dims[2] = {HQ * DH, DM};
        cuuint64_t str[1] = {HQ * DH * 2};
        cuuint32_t box[2] = {32, 256};
        make_map(fn, &tmWq, d_in[3], 2, dims, str, box, CU_TENSOR_MAP_SWIZZLE_64B, CU_TENSOR_MAP_L2_PROMOTION_L2_128B);
    }
    {
        cuuint64_t dims[3] = {64, HQ * DH, 8};
        cuuint64_t str[2] = {DM * 2, 128};
        cuuint32_t box[3] = {64, 32, 4};
        make_map(fn, &tmWo, d_in[4], 3, dims, str, box, CU_TENSOR_MAP_SWIZZLE_128B, CU_TENSOR_MAP_L2_PROMOTION_L2_256B);
    }
    {
        cuuint64_t dims[2] = {FF, DM};
        cuuint64_t str[1] = {FF * 2};
        cuuint32_t box[2] = {16, 256};
        make_map(fn, &tmWg, d_in[6], 2, dims, str, box, CU_TENSOR_MAP_SWIZZLE_32B, CU_TENSOR_MAP_L2_PROMOTION_L2_128B);
        make_map(fn, &tmWu, d_in[7], 2, dims, str, box, CU_TENSOR_MAP_SWIZZLE_32B, CU_TENSOR_MAP_L2_PROMOTION_L2_128B);
    }
    {
        cuuint64_t dims[3] = {64, FF, 8};
        cuuint64_t str[2] = {DM * 2, 128};
        cuuint32_t box[3] = {64, 16, 8};
        make_map(fn, &tmWd, d_in[8], 3, dims, str, box, CU_TENSOR_MAP_SWIZZLE_128B, CU_TENSOR_MAP_L2_PROMOTION_L2_256B);
    }
    fused_kernel<<<NCTA, NTHREADS, SM_TOTAL>>>(tmK, tmV, tmWq, tmWo, tmWg, tmWu, tmWd,
                                               (const bf16*)d_in[0], (const bf16*)d_in[9], (const bf16*)d_in[10], (bf16*)d_out);
}
```

```cpp
#include <cuda_runtime.h>
#include <cuda_bf16.h>
#include <cuda.h>
#include <stdint.h>

typedef __nv_bfloat16 bf16;

constexpr int NB = 4, DM = 512, HQ = 32, HKV = 8, SK = 16384, DH = 128, WIN = 4096, FF = 1792;
constexpr int NCTA = 128;
constexpr int NFFN = 112;
constexpr int KEYS_PER_CTA = 1024;
constexpr int TILE_KEYS = 64;
constexpr int NTILE = KEYS_PER_CTA / TILE_KEYS;
constexpr int SLOT_BYTES = 16384;
#define NSLOT 12
#define INFLIGHT 4
#define INFLIGHT1 2
#define NFREE 4
#define PACE_T0 3000
#define PACE_DT 650
#define DEEP INFLIGHT
#define GATE_GU 0
#define TMPF 0
#define PREWRITE 1
#define REH_IT 3
#define BACKOFF 0
#define P_WO 32
#define P_GU 32
#define P_DN 32
constexpr int NFRONT = 4;
constexpr int NSEQ = NFRONT + 2 * NTILE + 5;
constexpr int NCONS = 256;
constexpr int NTHREADS = NCONS + 32;

__host__ __device__ constexpr int kv2pos(int kv) {
    return NFRONT + kv + (kv >= P_WO ? 2 : 0) + (kv >= P_GU ? 2 : 0) + (kv >= P_DN ? 1 : 0);
}
__host__ __device__ constexpr int posK(int i) { return kv2pos(i == 0 ? 0 : 2 * i - 1); }
__host__ __device__ constexpr int posV(int i) { return kv2pos(i == NTILE - 1 ? 2 * NTILE - 1 : 2 * i + 2); }
constexpr int POS_WO = NFRONT + P_WO;
constexpr int POS_GU = NFRONT + P_GU + 2;
constexpr int POS_DN = NFRONT + P_DN + 4;
static_assert(P_WO <= P_GU && P_GU <= P_DN && P_DN <= 32, "order");
static_assert(POS_WO >= NSEQ - NSLOT, "tail weights must never need to be recycled");

__device__ unsigned g_epoch;
__device__ __align__(128) unsigned g_llmod[6 * NCTA * 16];
__device__ __align__(128) unsigned g_llq[NB * HQ * DH];
__device__ __align__(128) unsigned g_llo[NCTA * 16 * 40];
__device__ __align__(128) unsigned g_ll2[NCTA * NCTA * 16];
__device__ __align__(128) unsigned g_ll3[NCTA * 16];
__device__ __align__(128) unsigned g_ll4[NCTA * NFFN * 16];
#define STAMP(i)
#define PSTAMP(i)
#define DSTAMP(i, dep)
#define CSTAMP(i)

__device__ __forceinline__ uint32_t smem_u32(const void* p) { return (uint32_t)__cvta_generic_to_shared(p); }
__device__ __forceinline__ uint32_t bfr_hi(float x) {
    uint32_t r; asm("cvt.rn.bf16x2.f32 %0, %1, %2;" : "=r"(r) : "f"(x), "f"(0.f)); return r;
}
__device__ __forceinline__ float bfr(float x) { return __uint_as_float(bfr_hi(x)); }
__device__ __forceinline__ float bf_lo(uint32_t u) { return __uint_as_float(u << 16); }
__device__ __forceinline__ float bf_hi(uint32_t u) { return __uint_as_float(u & 0xffff0000u); }
__device__ __forceinline__ uint32_t pack_bf2(float lo, float hi) {
    uint32_t r; asm("cvt.rn.bf16x2.f32 %0, %1, %2;" : "=r"(r) : "f"(hi), "f"(lo)); return r;
}

__device__ __forceinline__ void mbar_init(uint32_t bar, uint32_t cnt) {
    asm volatile("mbarrier.init.shared::cta.b64 [%0], %1;" :: "r"(bar), "r"(cnt) : "memory");
}
__device__ __forceinline__ void mbar_expect_tx(uint32_t bar, uint32_t bytes) {
    asm volatile("mbarrier.arrive.expect_tx.shared::cta.b64 _, [%0], %1;" :: "r"(bar), "r"(bytes) : "memory");
}
__device__ __forceinline__ void mbar_arrive(uint32_t bar) {
    asm volatile("mbarrier.arrive.shared::cta.b64 _, [%0];" :: "r"(bar) : "memory");
}
__device__ __forceinline__ bool mbar_try(uint32_t bar, uint32_t parity) {
    uint32_t ok;
    asm volatile("{\n\t.reg .pred p;\n\tmbarrier.try_wait.parity.shared::cta.b64 p, [%1], %2;\n\tselp.u32 %0, 1, 0, p;\n\t}"
                 : "=r"(ok) : "r"(bar), "r"(parity) : "memory");
    return ok != 0;
}
__device__ __forceinline__ bool mbar_test(uint32_t bar, uint32_t parity) {
    uint32_t ok;
    asm volatile("{\n\t.reg .pred p;\n\tmbarrier.test_wait.parity.shared::cta.b64 p, [%1], %2;\n\tselp.u32 %0, 1, 0, p;\n\t}"
                 : "=r"(ok) : "r"(bar), "r"(parity) : "memory");
    return ok != 0;
}
__device__ __forceinline__ bool expired(unsigned t0c) { return (unsigned)clock() - t0c > (1u << 24); }
__device__ __forceinline__ void mbar_wait(unsigned t0c, uint32_t bar, uint32_t parity) {
#pragma unroll 1
    while (!mbar_try(bar, parity)) if (expired(t0c)) return;
}
__device__ __forceinline__ void tma2d(uint32_t dst, const CUtensorMap* tm, int c0, int c1, uint32_t bar) {
    asm volatile("cp.async.bulk.tensor.2d.shared::cluster.global.tile.mbarrier::complete_tx::bytes [%0], [%1, {%3, %4}], [%2];"
                 :: "r"(dst), "l"((uint64_t)tm), "r"(bar), "r"(c0), "r"(c1) : "memory");
}
__device__ __forceinline__ void tma3d(uint32_t dst, const CUtensorMap* tm, int c0, int c1, int c2, uint32_t bar) {
    asm volatile("cp.async.bulk.tensor.3d.shared::cluster.global.tile.mbarrier::complete_tx::bytes [%0], [%1, {%3, %4, %5}], [%2];"
                 :: "r"(dst), "l"((uint64_t)tm), "r"(bar), "r"(c0), "r"(c1), "r"(c2) : "memory");
}
__device__ __forceinline__ void tma3d_hint(uint32_t dst, const CUtensorMap* tm, int c0, int c1, int c2, uint32_t bar, uint64_t pol) {
    asm volatile("cp.async.bulk.tensor.3d.shared::cluster.global.tile.mbarrier::complete_tx::bytes.L2::cache_hint [%0], [%1, {%3, %4, %5}], [%2], %6;"
                 :: "r"(dst), "l"((uint64_t)tm), "r"(bar), "r"(c0), "r"(c1), "r"(c2), "l"(pol) : "memory");
}
__device__ __forceinline__ void ldsm4(uint32_t (&r)[4], uint32_t addr) {
    asm volatile("ldmatrix.sync.aligned.m8n8.x4.shared.b16 {%0,%1,%2,%3}, [%4];"
                 : "=r"(r[0]), "=r"(r[1]), "=r"(r[2]), "=r"(r[3]) : "r"(addr) : "memory");
}
__device__ __forceinline__ void ldsm4t(uint32_t (&r)[4], uint32_t addr) {
    asm volatile("ldmatrix.sync.aligned.m8n8.x4.trans.shared.b16 {%0,%1,%2,%3}, [%4];"
                 : "=r"(r[0]), "=r"(r[1]), "=r"(r[2]), "=r"(r[3]) : "r"(addr) : "memory");
}
__device__ __forceinline__ void mma16816(float (&c)[4], const uint32_t (&a)[4], uint32_t b0, uint32_t b1) {
    asm volatile("mma.sync.aligned.m16n8k16.row.col.f32.bf16.bf16.f32 {%0,%1,%2,%3}, {%4,%5,%6,%7}, {%8,%9}, {%0,%1,%2,%3};"
                 : "+f"(c[0]), "+f"(c[1]), "+f"(c[2]), "+f"(c[3])
                 : "r"(a[0]), "r"(a[1]), "r"(a[2]), "r"(a[3]), "r"(b0), "r"(b1));
}
__device__ __forceinline__ uint32_t movm_t(uint32_t a) {
    uint32_t d; asm volatile("movmatrix.sync.aligned.m8n8.trans.b16 %0, %1;" : "=r"(d) : "r"(a)); return d;
}
__device__ __forceinline__ float ex2(float x) {
    float r; asm("ex2.approx.ftz.f32 %0, %1;" : "=f"(r) : "f"(x * 1.4426950408889634f)); return r;
}
__device__ __forceinline__ void cons_sync() { asm volatile("bar.sync 1, 256;" ::: "memory"); }

__device__ __forceinline__ uint4 ld_rlx4(const unsigned* p) {
    uint4 v;
    asm volatile("ld.relaxed.gpu.global.v4.u32 {%0,%1,%2,%3}, [%4];" : "=r"(v.x), "=r"(v.y), "=r"(v.z), "=r"(v.w) : "l"(p) : "memory");
    return v;
}
__device__ __forceinline__ uint2 ld_rlx2(const unsigned* p) {
    uint2 v;
    asm volatile("ld.relaxed.gpu.global.v2.u32 {%0,%1}, [%2];" : "=r"(v.x), "=r"(v.y) : "l"(p) : "memory");
    return v;
}
__device__ __forceinline__ void st_rlx(unsigned* p, unsigned v) {
    asm volatile("st.relaxed.gpu.global.u32 [%0], %1;" :: "l"(p), "r"(v) : "memory");
}
__device__ __forceinline__ void st_rlx2(unsigned* p, unsigned a, unsigned b) {
    asm volatile("st.relaxed.gpu.global.v2.u32 [%0], {%1,%2};" :: "l"(p), "r"(a), "r"(b) : "memory");
}
__device__ __forceinline__ bool tag_ok(const uint4& v, unsigned tag, unsigned mask) {
    return (((v.x ^ tag) | (v.y ^ tag) | (v.z ^ tag) | (v.w ^ tag)) & mask) == 0;
}
__device__ __forceinline__ uint4 poll4(unsigned t0c, const unsigned* p, unsigned tag, unsigned mask) {
    uint4 v = ld_rlx4(p);
#pragma unroll 1
    while (!tag_ok(v, tag, mask) && !expired(t0c)) { if (BACKOFF) __nanosleep(BACKOFF); v = ld_rlx4(p); }
    return v;
}
__device__ __forceinline__ void poll4x2(unsigned t0c, const unsigned* p0, const unsigned* p1, unsigned tag, unsigned mask, uint4& a, uint4& b) {
    if (mask == 0) { a = b = make_uint4(0x3f800000u, 0x3f800000u, 0x3f800000u, 0x3f800000u); return; }
    a = ld_rlx4(p0); b = ld_rlx4(p1);
#pragma unroll 1
    while (true) {
        bool oa = tag_ok(a, tag, mask), ob = tag_ok(b, tag, mask);
        if ((oa && ob) || expired(t0c)) break;
        if (BACKOFF) __nanosleep(BACKOFF);
        if (!oa) a = ld_rlx4(p0);
        if (!ob) b = ld_rlx4(p1);
    }
}
__device__ __forceinline__ unsigned tagf(float v, unsigned tag4) { return (__float_as_uint(v) & ~0xFu) | tag4; }
__device__ __forceinline__ float untagf(unsigned u) { return __uint_as_float(u); }
__device__ __forceinline__ float red8x4(float v0, float v1, float v2, float v3, int lane) {
    const bool h4 = lane & 16, h3 = lane & 8;
    const float k0 = (h4 ? v2 : v0) + __shfl_xor_sync(0xffffffffu, h4 ? v0 : v2, 16);
    const float k1 = (h4 ? v3 : v1) + __shfl_xor_sync(0xffffffffu, h4 ? v1 : v3, 16);
    float k = (h3 ? k1 : k0) + __shfl_xor_sync(0xffffffffu, h3 ? k0 : k1, 8);
    return k + __shfl_xor_sync(0xffffffffu, k, 4);
}

constexpr int SM_RING = 0;
constexpr int SM_MISC = NSLOT * SLOT_BYTES;
constexpr int ACT_PITCH = 520;
constexpr int SM_OBUF  = SM_MISC;
constexpr int OB_HP = 136, OB_WP = 4 * OB_HP;
constexpr int SM_ACT   = SM_OBUF + 8 * OB_WP * 4;
constexpr int SM_QS    = SM_ACT + 4 * ACT_PITCH * 2;
constexpr int SM_RED   = SM_QS + 4 * 136 * 2;
constexpr int SM_ML    = SM_RED + 3 * 8 * 32 * 4;
constexpr int SM_ST    = SM_ML + 8 * 4 * 2 * 4;
constexpr int SM_BAR   = SM_ST + 64 * 4;
constexpr int SM_TOTAL = SM_BAR + 2 * NSLOT * 8 + 32;
static_assert(SM_TOTAL <= 232448, "smem");

__device__ __noinline__ float gemv32(uint32_t a0, uint32_t a1, uint32_t ks_stride, const bf16* act_s, float* obuf) {
    const int tid = threadIdx.x, warp = tid >> 5, lane = tid & 31, g = lane >> 2, t = lane & 3;
    float acc[2][4] = {};
#pragma unroll
    for (int ks = 0; ks < 4; ks++) {
        const int k0 = warp * 64 + ks * 16;
        uint32_t b0 = 0, b1 = 0;
        if (g < 4) {
            b0 = *(const uint32_t*)(act_s + g * ACT_PITCH + k0 + 2 * t);
            b1 = *(const uint32_t*)(act_s + g * ACT_PITCH + k0 + 2 * t + 8);
        }
        uint32_t a[4], a2[4];
        ldsm4t(a, a0 + ks * ks_stride);
        ldsm4t(a2, a1 + ks * ks_stride);
        mma16816(acc[0], a, b0, b1);
        mma16816(acc[1], a2, b0, b1);
    }
    if (t < 2) {
#pragma unroll
        for (int mt = 0; mt < 2; mt++) {
            obuf[warp * 128 + (2 * t) * 32 + mt * 16 + g] = acc[mt][0];
            obuf[warp * 128 + (2 * t + 1) * 32 + mt * 16 + g] = acc[mt][1];
            obuf[warp * 128 + (2 * t) * 32 + mt * 16 + g + 8] = acc[mt][2];
            obuf[warp * 128 + (2 * t + 1) * 32 + mt * 16 + g + 8] = acc[mt][3];
        }
    }
    cons_sync();
    float s = 0.f;
    if (tid < 128) {
        const float* p = obuf + tid;
        s = ((p[0] + p[128]) + (p[256] + p[384])) + ((p[512] + p[640]) + (p[768] + p[896]));
    }
    return s;
}
__device__ __forceinline__ uint32_t pk_lo(const uint4& a) { return (a.x >> 16) | (a.y & 0xffff0000u); }
__device__ __forceinline__ uint32_t pk_hi(const uint4& a) { return (a.z >> 16) | (a.w & 0xffff0000u); }

__device__ __forceinline__ void
fused_body(const CUtensorMap& tmK, const CUtensorMap& tmV, const CUtensorMap& tmWq, const CUtensorMap& tmWo,
           const CUtensorMap& tmWg, const CUtensorMap& tmWu, const CUtensorMap& tmWd, const CUtensorMap& tmWm,
           const bf16* __restrict__ x, const bf16* __restrict__ cvec, bf16* __restrict__ out)
{
    extern __shared__ __align__(1024) uint8_t smem[];
    const uint32_t sbase = smem_u32(smem);
    const int tid = threadIdx.x, warp = tid >> 5, lane = tid & 31;
    const unsigned t0c = (unsigned)clock();
    const int j = blockIdx.x;
    const int ab = j >> 5, ag = (j >> 2) & 7, as = j & 3;
    const uint32_t bar_full = sbase + SM_BAR, bar_empty = bar_full + NSLOT * 8;
    const uint32_t bar_qdone = bar_empty + NSLOT * 8, bar_t1 = bar_qdone + 8;
    const int modG = j < 64 ? j : 2 * j - 64;

    if (warp == 8) {
        if (lane == 0) {
            PSTAMP(16);
            if (sbase & 1023u) __trap();
            for (int s = 0; s < NSLOT; s++) { mbar_init(bar_full + s * 8, 1); mbar_init(bar_empty + s * 8, 4); }
            mbar_init(bar_qdone, 1); mbar_init(bar_t1, 1);
            asm volatile("fence.mbarrier_init.release.cluster;" ::: "memory");
            asm volatile("fence.proxy.async.shared::cta;" ::: "memory");
        }
        __syncwarp();
        asm volatile("bar.arrive 2, 288;" ::: "memory");
        if (lane == 0) {
            uint64_t pol;
            asm volatile("createpolicy.fractional.L2::evict_first.b64 %0, 1.0;" : "=l"(pol));
            const int row0 = (ab * HKV + ag) * SK + (SK - WIN) + as * KEYS_PER_CTA;
            int kv = 0;
            bool qdone = false;
            unsigned tg0; asm volatile("mov.u32 %0, %globaltimer_lo;" : "=r"(tg0));
            auto skipped = [&](int p) {
                return (p == 1 && j < 64) || ((p == POS_GU || p == POS_GU + 1 || p == POS_DN) && j >= NFFN);
            };
#pragma unroll 1
            for (int pos = 0; pos < NSEQ; pos++) {
                const int slot = pos % NSLOT, use = pos / NSLOT;
                const uint32_t dst = sbase + SM_RING + slot * SLOT_BYTES, fb = bar_full + slot * 8;
                if (skipped(pos)) { if (pos == 1) mbar_arrive(fb); continue; }
                if (!qdone) qdone = mbar_test(bar_qdone, 0);
                int depth = qdone ? INFLIGHT : INFLIGHT1;
                if (DEEP != INFLIGHT && qdone) {
                    unsigned now; asm volatile("mov.u32 %0, %globaltimer_lo;" : "=r"(now));
                    if ((int)(now - tg0) > PACE_T0 + (pos - NFRONT) * PACE_DT) depth = DEEP;
                }
                if (pos >= NFREE && depth < NSLOT) {
                    const int p2 = pos - depth;
                    if (!skipped(p2)) mbar_wait(t0c, bar_full + (p2 % NSLOT) * 8, (p2 / NSLOT) & 1);
                }
                if (use > 0) mbar_wait(t0c, bar_empty + slot * 8, (use - 1) & 1);
                if (GATE_GU && pos == POS_GU) mbar_wait(t0c, bar_t1, 0);
                mbar_expect_tx(fb, SLOT_BYTES);
                if (pos < 2 || pos == POS_GU || pos == POS_GU + 1) {
                    const CUtensorMap* tm = pos < 2 ? &tmWm : (pos == POS_GU ? &tmWg : &tmWu);
                    const int c0 = pos < 2 ? 16 * (modG + pos) : 16 * j;
                    tma2d(dst, tm, c0, 0, fb);
                    tma2d(dst + 8192, tm, c0, 256, fb);
                } else if (pos < 4) {
                    tma2d(dst, &tmWq, 32 * j, 256 * (pos - 2), fb);
                } else if (pos == POS_WO || pos == POS_WO + 1) {
                    tma3d(dst, &tmWo, 0, 32 * j, 4 * (pos - POS_WO), fb);
                } else if (pos == POS_DN) {
                    tma3d(dst, &tmWd, 0, 16 * j, 0, fb);
                } else {
                    const bool isK = (kv == 0) || ((kv & 1) && kv < 2 * NTILE - 1);
                    const int ti = isK ? ((kv + 1) >> 1) : (kv == 2 * NTILE - 1 ? NTILE - 1 : (kv >> 1) - 1);
                    tma3d_hint(dst, isK ? &tmK : &tmV, 0, row0 + ti * TILE_KEYS, 0, fb, pol);
                    kv++;
                }
                if (pos == 3) PSTAMP(24);
                if (pos == 6) PSTAMP(25);
                if (pos == 10) PSTAMP(26);
                if (pos == 14) PSTAMP(27);
            }
            PSTAMP(17);
        }
        return;
    }

    STAMP(0);
    float* obuf = (float*)(smem + SM_OBUF);
    bf16* act_s = (bf16*)(smem + SM_ACT);
    bf16* qs = (bf16*)(smem + SM_QS);
    float* red = (float*)(smem + SM_RED);
    float* mls = (float*)(smem + SM_ML);
    float* st = (float*)(smem + SM_ST);
    const int g = lane >> 2, t = lane & 3;
    const int mi = lane >> 3, lr = lane & 7;
    const int ub = tid & 3, uj = tid >> 2;

    unsigned epoch;
    asm volatile("ld.relaxed.gpu.global.u32 %0, [%1];" : "=r"(epoch) : "l"(&g_epoch) : "memory");
    const uint2 cu0 = __ldg((const uint2*)(cvec + ub * DM + 4 * uj)), cu1 = __ldg((const uint2*)(cvec + ub * DM + 4 * (uj + 64)));
    const uint2 xu0 = __ldg((const uint2*)(x + ub * DM + 4 * uj)), xu1 = __ldg((const uint2*)(x + ub * DM + 4 * (uj + 64)));
    float xown = 0.f;
    if (tid < 16) xown = __bfloat162float(x[(tid >> 2) * DM + 4 * j + (tid & 3)]);
    unsigned* const mod_dst = &g_llmod[(modG * 4 + ((tid & 31) >> 2)) * 16 + (tid >> 5) * 4 + (tid & 3)];
    unsigned* const q_dst = &g_llq[(tid >> 5) * (HQ * DH) + 32 * j + (tid & 31)];
    const bool mod_pub = tid < 128 && (j >= 64 || (tid & 31) < 16);
    if (mod_pub) st_rlx(mod_dst, 0u);
    if (tid < 128) st_rlx(q_dst, 0u);
    if (warp < 4) {
        const uint4* xp = (const uint4*)(x + warp * DM);
        uint4 u0 = __ldg(xp + lane), u1 = __ldg(xp + 32 + lane);
        uint32_t w[8] = {u0.x, u0.y, u0.z, u0.w, u1.x, u1.y, u1.z, u1.w};
        float s = 0.f;
#pragma unroll
        for (int i = 0; i < 8; i++) s += bf_lo(w[i]) + bf_hi(w[i]);
#pragma unroll
        for (int o = 16; o; o >>= 1) s += __shfl_xor_sync(0xffffffffu, s, o);
        const float mean = s * (1.f / DM);
        float q = 0.f;
#pragma unroll
        for (int i = 0; i < 8; i++) { float a = bf_lo(w[i]) - mean, b2 = bf_hi(w[i]) - mean; q += a * a + b2 * b2; }
#pragma unroll
        for (int o = 16; o; o >>= 1) q += __shfl_xor_sync(0xffffffffu, q, o);
        if (lane == 0) {
            st[warp] = bfr(mean);
            st[4 + warp] = __frcp_rn(bfr(__fsqrt_rn(bfr(bfr(q * (1.f / DM)) + 1e-5f))));
        }
    }
    {
        auto silu2 = [](uint32_t u) {
            const float a = bf_lo(u), b = bf_hi(u);
            return pack_bf2(__fdividef(a, 1.f + __expf(-a)), __fdividef(b, 1.f + __expf(-b)));
        };
        *(uint2*)(act_s + ub * ACT_PITCH + 4 * uj) = make_uint2(silu2(cu0.x), silu2(cu0.y));
        *(uint2*)(act_s + ub * ACT_PITCH + 4 * (uj + 64)) = make_uint2(silu2(cu1.x), silu2(cu1.y));
    }
    const unsigned tag16 = 1u + epoch % 65535u, tag4 = 1u + epoch % 15u;
    asm volatile("bar.sync 2, 288;" ::: "memory");
    STAMP(18);

    const uint32_t off32 = (uint32_t)((warp * 64 + lr + (mi >> 1) * 8) * 32 + (((mi & 1) ^ ((lr >> 2) & 1)) << 4));
    {
        mbar_wait(t0c, bar_full, 0);
        if (j >= 64) mbar_wait(t0c, bar_full + 8, 0);
        STAMP(19);
        const float s = gemv32(sbase + SM_RING + off32, sbase + SM_RING + SLOT_BYTES + off32, 512, act_s, obuf);
        if (mod_pub) st_rlx(mod_dst, bfr_hi(s) | tag16);
        if (tid < 128 && lane == 0) { mbar_arrive(bar_empty); mbar_arrive(bar_empty + 8); }
    }
    STAMP(1);
    {
        const float mu = st[ub], sd = st[4 + ub];
#pragma unroll
        for (int i = 0; i < 2; i++) {
            uint4 a, b;
            poll4x2(t0c, &g_llmod[(uj + 64 * i) * 16 + ub * 4], &g_llmod[NCTA * 16 + (uj + 64 * i) * 16 + ub * 4], tag16, 0xffffu, a, b);
            const uint2 xu = i ? xu1 : xu0;
            const float h0 = bfr(bfr(bfr(bf_lo(xu.x) - mu) * sd) * bfr(1.f + bf_hi(b.x))) + bf_hi(a.x);
            const float h1 = bfr(bfr(bfr(bf_hi(xu.x) - mu) * sd) * bfr(1.f + bf_hi(b.y))) + bf_hi(a.y);
            const float h2 = bfr(bfr(bfr(bf_lo(xu.y) - mu) * sd) * bfr(1.f + bf_hi(b.z))) + bf_hi(a.z);
            const float h3 = bfr(bfr(bfr(bf_hi(xu.y) - mu) * sd) * bfr(1.f + bf_hi(b.w))) + bf_hi(a.w);
            *(uint2*)(act_s + ub * ACT_PITCH + 4 * (uj + 64 * i)) = make_uint2(pack_bf2(h0, h1), pack_bf2(h2, h3));
        }
    }
    mbar_wait(t0c, bar_full + (2 + (warp >> 2)) * 8, 0);
    cons_sync();
    STAMP(2);
    {
        const int row = (warp & 3) * 64 + lr + (mi >> 1) * 8;
        const uint32_t base = sbase + SM_RING + (2 + (warp >> 2)) * SLOT_BYTES + row * 64;
        const int sw = (row >> 1) & 3;
        const float s = gemv32(base + (((mi & 1) ^ sw) << 4), base + (((2 + (mi & 1)) ^ sw) << 4), 1024, act_s, obuf);
        if (tid < 128) {
            st_rlx(q_dst, bfr_hi(s) | tag16);
            if (lane == 0) { mbar_arrive(bar_empty + 16); mbar_arrive(bar_empty + 24); }
        }
    }
    STAMP(3);
    uint32_t sbp[2][2], cbp[2][2];
    float gav = 0.f, gbv = 0.f;
#pragma unroll
    for (int i = 0; i < 2; i++) {
        uint4 a, b;
        poll4x2(t0c, &g_llmod[3 * NCTA * 16 + (uj + 64 * i) * 16 + ub * 4], &g_llmod[4 * NCTA * 16 + (uj + 64 * i) * 16 + ub * 4], tag16, 0xffffu, a, b);
        sbp[i][0] = pk_lo(a); sbp[i][1] = pk_hi(a);
        cbp[i][0] = pack_bf2(1.f + bf_hi(b.x), 1.f + bf_hi(b.y)); cbp[i][1] = pack_bf2(1.f + bf_hi(b.z), 1.f + bf_hi(b.w));
    }
    if (tid < 16) {
        uint4 a, b;
        poll4x2(t0c, &g_llmod[2 * NCTA * 16 + j * 16 + (tid >> 2) * 4], &g_llmod[5 * NCTA * 16 + j * 16 + (tid >> 2) * 4], tag16, 0xffffu, a, b);
        const int c = tid & 3;
        gav = bf_hi(c == 0 ? a.x : c == 1 ? a.y : c == 2 ? a.z : a.w);
        gbv = bf_hi(c == 0 ? b.x : c == 1 ? b.y : c == 2 ? b.z : b.w);
    }
    if (tid >= 128) {
        const int u = tid - 128;
        uint4 a = poll4(t0c, &g_llq[ab * (HQ * DH) + ag * 512 + u * 4], tag16, 0xffffu);
        *(uint2*)(qs + (u >> 5) * 136 + (u & 31) * 4) = make_uint2(pk_lo(a), pk_hi(a));
    }
    cons_sync();
    if (tid == 32) mbar_arrive(bar_qdone);
    uint32_t qf[8][2];
#pragma unroll
    for (int ks = 0; ks < 8; ks++) {
        qf[ks][0] = 0; qf[ks][1] = 0;
        if (g < 4) {
            qf[ks][0] = *(const uint32_t*)(qs + g * 136 + ks * 16 + 2 * t);
            qf[ks][1] = *(const uint32_t*)(qs + g * 136 + ks * 16 + 2 * t + 8);
        }
    }
    STAMP(4);

    float o[8][4];
#pragma unroll
    for (int i = 0; i < 8; i++) { o[i][0] = o[i][1] = o[i][2] = o[i][3] = 0.f; }
    float m0 = -INFINITY, m1 = -INFINITY, l0 = 0.f, l1 = 0.f;

#pragma unroll 1
    for (int pass = (PREWRITE ? 0 : 1); pass < 2; pass++) {
    const bool real = pass != 0;
    {
        const int w4 = warp & 3, grp = warp >> 2;
        const int keyK = w4 * 16 + lr + (mi & 1) * 8, chK = mi >> 1;
        const int keyV = w4 * 16 + lr + (mi >> 1) * 8, chV = mi & 1;
        const uint32_t offK = keyK * 128, offV = keyV * 128;
        const int it0 = (real && PREWRITE) ? REH_IT : 0, it1 = real ? NTILE / 2 : REH_IT;
#pragma unroll 1
        for (int it = it0; it < it1; it++) {
            const int ti = 2 * it + grp;
            const int pk = posK(ti), pv = posV(ti);
            const int sk = pk % NSLOT, sv = pv % NSLOT;
            mbar_wait(t0c, bar_full + sk * 8, (pk / NSLOT) & 1);
            float s0[4] = {0.f, 0.f, 0.f, 0.f}, s1[4] = {0.f, 0.f, 0.f, 0.f};
            const uint32_t kb = sbase + SM_RING + sk * SLOT_BYTES + offK;
#pragma unroll
            for (int ks = 0; ks < 4; ks++) {
                uint32_t a[4], a2[4];
                const uint32_t sw = (uint32_t)(((2 * ks + chK) ^ lr) << 4);
                ldsm4(a, kb + sw);
                ldsm4(a2, kb + 8192 + sw);
                mma16816(s0, a, qf[ks][0], qf[ks][1]);
                mma16816(s1, a2, qf[4 + ks][0], qf[4 + ks][1]);
            }
            __syncwarp();
            if (lane == 0) mbar_arrive(bar_empty + sk * 8);
            float sv4[4];
#pragma unroll
            for (int i = 0; i < 4; i++) sv4[i] = bfr(bfr(s0[i] + s1[i]) * 0.08838834764831845f);
            float x0 = fmaxf(sv4[0], sv4[2]), x1 = fmaxf(sv4[1], sv4[3]);
#pragma unroll
            for (int off = 4; off < 32; off <<= 1) {
                x0 = fmaxf(x0, __shfl_xor_sync(0xffffffffu, x0, off));
                x1 = fmaxf(x1, __shfl_xor_sync(0xffffffffu, x1, off));
            }
            const float n0 = fmaxf(m0, x0), n1 = fmaxf(m1, x1);
            if (__any_sync(0xffffffffu, n0 > m0 || n1 > m1)) {
                const float f0 = ex2(m0 - n0), f1 = ex2(m1 - n1);
                l0 *= f0; l1 *= f1;
#pragma unroll
                for (int i = 0; i < 8; i++) { o[i][0] *= f0; o[i][1] *= f1; o[i][2] *= f0; o[i][3] *= f1; }
                m0 = n0; m1 = n1;
            }
            const float p0 = ex2(sv4[0] - m0), p1 = ex2(sv4[1] - m1);
            const float p2 = ex2(sv4[2] - m0), p3 = ex2(sv4[3] - m1);
            l0 += p0 + p2; l1 += p1 + p3;
            const uint32_t pb0 = movm_t(pack_bf2(p0, p1)), pb1 = movm_t(pack_bf2(p2, p3));
            mbar_wait(t0c, bar_full + sv * 8, (pv / NSLOT) & 1);
            const uint32_t vb = sbase + SM_RING + sv * SLOT_BYTES + offV;
#pragma unroll
            for (int mt = 0; mt < 8; mt++) {
                uint32_t a[4];
                ldsm4t(a, vb + (mt >> 2) * 8192 + (uint32_t)(((2 * (mt & 3) + chV) ^ lr) << 4));
                mma16816(o[mt], a, pb0, pb1);
            }
            __syncwarp();
            if (lane == 0) mbar_arrive(bar_empty + sv * 8);
        }
    }
    STAMP(5);
    const unsigned tg4 = real ? tag4 : 0u, tg16 = real ? tag16 : 0u;
    const unsigned mk4 = real ? 0xfu : 0u, mk16 = real ? 0xffffu : 0u;
    {
        float la = l0, lb = l1;
#pragma unroll
        for (int off = 4; off < 32; off <<= 1) {
            la += __shfl_xor_sync(0xffffffffu, la, off);
            lb += __shfl_xor_sync(0xffffffffu, lb, off);
        }
        if (t < 2) {
            if (g == 0) {
                *(float2*)(mls + (2 * t) * 16 + warp * 2) = make_float2(m0, la);
                *(float2*)(mls + (2 * t + 1) * 16 + warp * 2) = make_float2(m1, lb);
            }
            float* ob = obuf + warp * OB_WP + 2 * t * OB_HP + g;
#pragma unroll
            for (int mt = 0; mt < 8; mt++) {
                ob[mt * 16] = o[mt][0]; ob[OB_HP + mt * 16] = o[mt][1];
                ob[mt * 16 + 8] = o[mt][2]; ob[OB_HP + mt * 16 + 8] = o[mt][3];
            }
        }
        cons_sync();
        const int hd = tid >> 6, d = (tid & 63) * 2;
        float4 ml4[4];
#pragma unroll
        for (int w = 0; w < 4; w++) ml4[w] = *(const float4*)(mls + hd * 16 + w * 4);
        const float M = untagf(tagf(fmaxf(fmaxf(fmaxf(ml4[0].x, ml4[0].z), fmaxf(ml4[1].x, ml4[1].z)), fmaxf(fmaxf(ml4[2].x, ml4[2].z), fmaxf(ml4[3].x, ml4[3].z))), tg4));
        float a0 = 0.f, a1 = 0.f, L = 0.f;
#pragma unroll
        for (int w = 0; w < 8; w++) {
            const float f = ex2(((w & 1) ? ml4[w >> 1].z : ml4[w >> 1].x) - M);
            const float2 v = *(const float2*)(obuf + w * OB_WP + hd * OB_HP + d);
            a0 += f * v.x; a1 += f * v.y;
            L += f * ((w & 1) ? ml4[w >> 1].w : ml4[w >> 1].y);
        }
        const int head = ag * 4 + hd, cons = head * 4 + (d >> 5);
        st_rlx2(&g_llo[((cons * 4 + ab) * 4 + as) * 40 + (d & 31)], tagf(a0, tg4), tagf(a1, tg4));
        if ((tid & 15) < 4) st_rlx2(&g_llo[((cons * 4 + ab) * 4 + as) * 40 + 32 + (tid & 15) * 2], tagf(M, tg4), tagf(L, tg4));
    }
    if (GATE_GU == 2 && real && tid == 32) mbar_arrive(bar_t1);
    STAMP(6);
    {
        if (tid < 128) {
            const int b = tid >> 5, s = (tid >> 3) & 3;
            const unsigned* seg = &g_llo[((j * 4 + b) * 4 + s) * 40];
            uint4 ov, ml;
            poll4x2(t0c, seg + (tid & 7) * 4, seg + 32, tag4, mk4, ov, ml);
            const float ms = untagf(ml.x);
            float M = fmaxf(ms, __shfl_xor_sync(0xffffffffu, ms, 8));
            M = fmaxf(M, __shfl_xor_sync(0xffffffffu, M, 16));
            const float e = ex2(ms - M);
            float L = e * untagf(ml.y);
            L += __shfl_xor_sync(0xffffffffu, L, 8);
            L += __shfl_xor_sync(0xffffffffu, L, 16);
            const float f = __fdividef(e, L);
            float v0 = f * untagf(ov.x), v1 = f * untagf(ov.y), v2 = f * untagf(ov.z), v3 = f * untagf(ov.w);
#pragma unroll
            for (int off = 8; off < 32; off <<= 1) {
                v0 += __shfl_xor_sync(0xffffffffu, v0, off); v1 += __shfl_xor_sync(0xffffffffu, v1, off);
                v2 += __shfl_xor_sync(0xffffffffu, v2, off); v3 += __shfl_xor_sync(0xffffffffu, v3, off);
            }
            if (lane < 8) *(uint2*)(qs + b * 136 + lane * 4) = make_uint2(pack_bf2(v0, v1), pack_bf2(v2, v3));
        }
        if (real) mbar_wait(t0c, bar_full + ((POS_WO + (warp >> 2)) % NSLOT) * 8, ((POS_WO + (warp >> 2)) / NSLOT) & 1);
        cons_sync();
        if (GATE_GU == 1 && real && tid == 32) mbar_arrive(bar_t1);
        STAMP(7);
        const uint32_t base = sbase + SM_RING + ((POS_WO + (warp >> 2)) % NSLOT) * SLOT_BYTES + (warp & 3) * 4096;
        float acc[4][4] = {};
#pragma unroll
        for (int ks = 0; ks < 2; ks++) {
            uint32_t b0 = 0, b1 = 0;
            if (g < 4) {
                b0 = *(const uint32_t*)(qs + g * 136 + ks * 16 + 2 * t);
                b1 = *(const uint32_t*)(qs + g * 136 + ks * 16 + 2 * t + 8);
            }
            const int row = ks * 16 + lr + (mi >> 1) * 8;
#pragma unroll
            for (int mt = 0; mt < 4; mt++) {
                uint32_t a[4];
                ldsm4t(a, base + row * 128 + (((2 * mt + (mi & 1)) ^ lr) << 4));
                mma16816(acc[mt], a, b0, b1);
            }
        }
        if (t < 2) {
#pragma unroll
            for (int mt = 0; mt < 4; mt++) {
                const int c0 = warp * 64 + mt * 16 + g, c1 = c0 + 8;
                st_rlx2(&g_ll2[((c0 >> 2) * NCTA + j) * 16 + (c0 & 3) * 4 + 2 * t], tagf(acc[mt][0], tg4), tagf(acc[mt][1], tg4));
                st_rlx2(&g_ll2[((c1 >> 2) * NCTA + j) * 16 + (c1 & 3) * 4 + 2 * t], tagf(acc[mt][2], tg4), tagf(acc[mt][3], tg4));
            }
        }
    }
    STAMP(8);
    float x1own = 0.f;
    {
        uint4 a, b;
        const unsigned* p = &g_ll2[j * (NCTA * 16) + tid * 4];
        poll4x2(t0c, p, p + 1024, tag4, mk4, a, b);
        float v0 = untagf(a.x) + untagf(b.x), v1 = untagf(a.y) + untagf(b.y), v2 = untagf(a.z) + untagf(b.z), v3 = untagf(a.w) + untagf(b.w);
        red[((lane >> 3) * 4 + (lane & 3)) * 8 + warp] = red8x4(v0, v1, v2, v3, lane);
        cons_sync();
        if (tid < 16) {
            const float4 r0 = *(const float4*)(red + tid * 8), r1 = *(const float4*)(red + tid * 8 + 4);
            const float s = ((r0.x + r0.y) + (r0.z + r0.w)) + ((r1.x + r1.y) + (r1.z + r1.w));
            x1own = bfr(xown + bfr(gav * bfr(s)));
            st_rlx(&g_ll3[j * 16 + tid], __float_as_uint(x1own) | tg16);
        }
    }
    STAMP(9);
    if (j < NFFN) {
        uint4 a, b;
        poll4x2(t0c, &g_ll3[tid * 4], &g_ll3[(tid + 256) * 4], tag16, mk16, a, b);
        STAMP(14);
        CSTAMP(1);
        float xv[8] = {bf_hi(a.x), bf_hi(a.y), bf_hi(a.z), bf_hi(a.w), bf_hi(b.x), bf_hi(b.y), bf_hi(b.z), bf_hi(b.w)};
        float mean = (((xv[0] + xv[1]) + (xv[2] + xv[3])) + ((xv[4] + xv[5]) + (xv[6] + xv[7]))) * 0.125f;
        float m2 = 0.f, m2b = 0.f;
#pragma unroll
        for (int i = 0; i < 4; i++) { m2 += (xv[i] - mean) * (xv[i] - mean); m2b += (xv[4 + i] - mean) * (xv[4 + i] - mean); }
        m2 += m2b;
        float n = 8.f;
#pragma unroll
        for (int off = 4; off < 32; off <<= 1) {
            const float om = __shfl_xor_sync(0xffffffffu, mean, off), o2 = __shfl_xor_sync(0xffffffffu, m2, off);
            const float dlt = om - mean;
            m2 = m2 + o2 + dlt * dlt * (n * 0.5f);
            mean = 0.5f * (mean + om);
            n *= 2.f;
        }
        if (lane < 4) { red[256 + lane * 16 + warp] = mean; red[256 + lane * 16 + 8 + warp] = m2; }
        CSTAMP(2);
        cons_sync();
        CSTAMP(3);
        const float4 a0 = *(const float4*)(red + 256 + ub * 16), a1 = *(const float4*)(red + 256 + ub * 16 + 4);
        const float4 q0 = *(const float4*)(red + 256 + ub * 16 + 8), q1 = *(const float4*)(red + 256 + ub * 16 + 12);
        const float mu = (((a0.x + a0.y) + (a0.z + a0.w)) + ((a1.x + a1.y) + (a1.z + a1.w))) * 0.125f;
        auto sq = [mu](float v) { return (v - mu) * (v - mu); };
        const float M2 = (((q0.x + q0.y) + (q0.z + q0.w)) + ((q1.x + q1.y) + (q1.z + q1.w))) +
                         64.f * (((sq(a0.x) + sq(a0.y)) + (sq(a0.z) + sq(a0.w))) + ((sq(a1.x) + sq(a1.y)) + (sq(a1.z) + sq(a1.w))));
        float sq_; asm("sqrt.approx.f32 %0, %1;" : "=f"(sq_) : "f"(bfr(bfr(M2 * (1.f / DM)) + 1e-5f)));
        const float mub = bfr(mu), sd = __fdividef(1.f, bfr(sq_));
#pragma unroll
        for (int i = 0; i < 2; i++) {
            float hv[4];
#pragma unroll
            for (int c = 0; c < 4; c++) {
                const uint32_t sw = sbp[i][c >> 1], cw = cbp[i][c >> 1];
                const float sbv = (c & 1) ? bf_hi(sw) : bf_lo(sw), cbv = (c & 1) ? bf_hi(cw) : bf_lo(cw);
                hv[c] = bfr(bfr(bfr(xv[i * 4 + c] - mub) * sd) * cbv) + sbv;
            }
            *(uint2*)(act_s + ub * ACT_PITCH + 4 * (uj + 64 * i)) = make_uint2(pack_bf2(hv[0], hv[1]), pack_bf2(hv[2], hv[3]));
        }
        CSTAMP(4);
        if (real) {
            mbar_wait(t0c, bar_full + (POS_GU % NSLOT) * 8, (POS_GU / NSLOT) & 1);
            mbar_wait(t0c, bar_full + ((POS_GU + 1) % NSLOT) * 8, ((POS_GU + 1) / NSLOT) & 1);
        }
        cons_sync();
        STAMP(10);
        CSTAMP(5);
        {
            float gs = gemv32(sbase + SM_RING + (POS_GU % NSLOT) * SLOT_BYTES + off32,
                              sbase + SM_RING + ((POS_GU + 1) % NSLOT) * SLOT_BYTES + off32, 512, act_s, obuf);
            if (tid < 128) {
                gs = bfr(gs);
                const float us = __shfl_xor_sync(0xffffffffu, gs, 16);
                const float inner = 0.7978845608028654f * (gs + 0.044715f * gs * gs * gs);
                const float ge = bfr(__fdividef(gs, 1.f + ex2(-2.f * inner)));
                if (lane < 16) ((unsigned short*)qs)[warp * 136 + lane] = (unsigned short)(bfr_hi(ge * us) >> 16);
            }
            if (real) mbar_wait(t0c, bar_full + (POS_DN % NSLOT) * 8, (POS_DN / NSLOT) & 1);
            cons_sync();
        }
        STAMP(11);
        CSTAMP(6);
        {
            uint32_t b0 = 0, b1 = 0;
            if (g < 4) {
                b0 = *(const uint32_t*)(qs + g * 136 + 2 * t);
                b1 = *(const uint32_t*)(qs + g * 136 + 2 * t + 8);
            }
            const int row = lr + (mi >> 1) * 8;
            const uint32_t base = sbase + SM_RING + (POS_DN % NSLOT) * SLOT_BYTES + warp * 2048 + row * 128;
#pragma unroll
            for (int mt = 0; mt < 4; mt++) {
                uint32_t af[4];
                float acc[4] = {0.f, 0.f, 0.f, 0.f};
                ldsm4t(af, base + (((2 * mt + (mi & 1)) ^ lr) << 4));
                mma16816(acc, af, b0, b1);
                if (t < 2) {
                    const int c0 = warp * 64 + mt * 16 + g, c1 = c0 + 8;
                    st_rlx2(&g_ll4[((c0 >> 2) * NFFN + j) * 16 + (c0 & 3) * 4 + 2 * t], tagf(acc[0], tg4), tagf(acc[1], tg4));
                    st_rlx2(&g_ll4[((c1 >> 2) * NFFN + j) * 16 + (c1 & 3) * 4 + 2 * t], tagf(acc[2], tg4), tagf(acc[3], tg4));
                }
            }
        }
    }
    STAMP(12);
    CSTAMP(7);
    {
        uint4 a, b;
        const unsigned* p = &g_ll4[j * (NFFN * 16) + tid * 4];
        const bool two = tid < 192;
        poll4x2(t0c, p, two ? p + 1024 : p, tag4, mk4, a, b);
        if (!two) b = make_uint4(0, 0, 0, 0);
        float v0 = untagf(a.x) + untagf(b.x), v1 = untagf(a.y) + untagf(b.y), v2 = untagf(a.z) + untagf(b.z), v3 = untagf(a.w) + untagf(b.w);
        red[512 + ((lane >> 3) * 4 + (lane & 3)) * 8 + warp] = red8x4(v0, v1, v2, v3, lane);
        cons_sync();
        if (tid < 16) {
            const int bb = tid >> 2, cc = tid & 3;
            const float4 r0 = *(const float4*)(red + 512 + tid * 8), r1 = *(const float4*)(red + 512 + tid * 8 + 4);
            const float s = ((r0.x + r0.y) + (r0.z + r0.w)) + ((r1.x + r1.y) + (r1.z + r1.w));
            const uint32_t r = bfr_hi(x1own + bfr(gbv * bfr(s)));
            if (real) ((unsigned short*)out)[bb * DM + 4 * j + cc] = (unsigned short)(r >> 16);
        }
        if (real && j == 0 && tid == 0) st_rlx(&g_epoch, epoch + 1);
    }
    STAMP(13);
    CSTAMP(0);
    if (!real) STAMP(15);
    }
}

__global__ void __launch_bounds__(NTHREADS, 1)
fused_kernel(const __grid_constant__ CUtensorMap tmK, const __grid_constant__ CUtensorMap tmV,
             const __grid_constant__ CUtensorMap tmWq, const __grid_constant__ CUtensorMap tmWo,
             const __grid_constant__ CUtensorMap tmWg, const __grid_constant__ CUtensorMap tmWu,
             const __grid_constant__ CUtensorMap tmWd, const __grid_constant__ CUtensorMap tmWm,
             const bf16* __restrict__ x, const bf16* __restrict__ cvec, bf16* __restrict__ out)
{
    fused_body(tmK, tmV, tmWq, tmWo, tmWg, tmWu, tmWd, tmWm, x, cvec, out);
}

typedef CUresult (*EncodeFn)(CUtensorMap*, CUtensorMapDataType, cuuint32_t, void*, const cuuint64_t*, const cuuint64_t*,
                             const cuuint32_t*, const cuuint32_t*, CUtensorMapInterleave, CUtensorMapSwizzle,
                             CUtensorMapL2promotion, CUtensorMapFloatOOBfill);

static void make_map(EncodeFn fn, CUtensorMap* m, void* ptr, int rank, const cuuint64_t* dims, const cuuint64_t* strides,
                     const cuuint32_t* box, CUtensorMapSwizzle sw, CUtensorMapL2promotion promo) {
    cuuint32_t es[3] = {1, 1, 1};
    fn(m, CU_TENSOR_MAP_DATA_TYPE_BFLOAT16, rank, ptr, dims, strides, box, es, CU_TENSOR_MAP_INTERLEAVE_NONE, sw, promo,
       CU_TENSOR_MAP_FLOAT_OOB_FILL_NONE);
}

extern "C" void kernel_launch(void* const* d_in, const int* in_sizes, int n_in, void* d_out, int out_size) {
    static EncodeFn fn = nullptr;
    if (!fn) {
        void* p = nullptr;
        cudaDriverEntryPointQueryResult qr;
        cudaGetDriverEntryPoint("cuTensorMapEncodeTiled", &p, cudaEnableDefault, &qr);
        fn = (EncodeFn)p;
        cudaFuncSetAttribute(fused_kernel, cudaFuncAttributeMaxDynamicSharedMemorySize, SM_TOTAL);
    }
    CUtensorMap tmK, tmV, tmWq, tmWo, tmWg, tmWu, tmWd, tmWm;
    {
        cuuint64_t dims[3] = {64, (cuuint64_t)NB * HKV * SK, 2};
        cuuint64_t str[2] = {256, 128};
        cuuint32_t box[3] = {64, TILE_KEYS, 2};
        make_map(fn, &tmK, d_in[1], 3, dims, str, box, CU_TENSOR_MAP_SWIZZLE_128B, CU_TENSOR_MAP_L2_PROMOTION_L2_256B);
        make_map(fn, &tmV, d_in[2], 3, dims, str, box, CU_TENSOR_MAP_SWIZZLE_128B, CU_TENSOR_MAP_L2_PROMOTION_L2_256B);
    }
    {
        cuuint64_t dims[2] = {HQ * DH, DM};
        cuuint64_t str[1] = {HQ * DH * 2};
        cuuint32_t box[2] = {32, 256};
        make_map(fn, &tmWq, d_in[3], 2, dims, str, box, CU_TENSOR_MAP_SWIZZLE_64B, CU_TENSOR_MAP_L2_PROMOTION_L2_128B);
    }
    {
        cuuint64_t dims[3] = {64, HQ * DH, 8};
        cuuint64_t str[2] = {DM * 2, 128};
        cuuint32_t box[3] = {64, 32, 4};
        make_map(fn, &tmWo, d_in[4], 3, dims, str, box, CU_TENSOR_MAP_SWIZZLE_128B, CU_TENSOR_MAP_L2_PROMOTION_L2_256B);
    }
    {
        cuuint64_t dims[2] = {FF, DM};
        cuuint64_t str[1] = {FF * 2};
        cuuint32_t box[2] = {16, 256};
        make_map(fn, &tmWg, d_in[6], 2, dims, str, box, CU_TENSOR_MAP_SWIZZLE_32B, CU_TENSOR_MAP_L2_PROMOTION_L2_128B);
        make_map(fn, &tmWu, d_in[7], 2, dims, str, box, CU_TENSOR_MAP_SWIZZLE_32B, CU_TENSOR_MAP_L2_PROMOTION_L2_128B);
    }
    {
        cuuint64_t dims[2] = {6 * DM, DM};
        cuuint64_t str[1] = {6 * DM * 2};
        cuuint32_t box[2] = {16, 256};
        make_map(fn, &tmWm, d_in[10], 2, dims, str, box, CU_TENSOR_MAP_SWIZZLE_32B, CU_TENSOR_MAP_L2_PROMOTION_L2_128B);
    }
    {
        cuuint64_t dims[3] = {64, FF, 8};
        cuuint64_t str[2] = {DM * 2, 128};
        cuuint32_t box[3] = {64, 16, 8};
        make_map(fn, &tmWd, d_in[8], 3, dims, str, box, CU_TENSOR_MAP_SWIZZLE_128B, CU_TENSOR_MAP_L2_PROMOTION_L2_256B);
    }
    fused_kernel<<<NCTA, NTHREADS, SM_TOTAL>>>(tmK, tmV, tmWq, tmWo, tmWg, tmWu, tmWd, tmWm,
                                               (const bf16*)d_in[0], (const bf16*)d_in[9], (bf16*)d_out);
}
```

```cpp
#include <cuda_runtime.h>
#include <cuda_bf16.h>
#include <cuda.h>
#include <stdint.h>

typedef __nv_bfloat16 bf16;

constexpr int NB = 4, DM = 512, HQ = 32, HKV = 8, SK = 16384, DH = 128, WIN = 4096, FF = 1792;
constexpr int NCTA = 128;
constexpr int NFFN = 112;
constexpr int NOWN = 32;
constexpr int KEYS_PER_CTA = 1024;
constexpr int TILE_KEYS = 64;
constexpr int NTILE = KEYS_PER_CTA / TILE_KEYS;
constexpr int SLOT_BYTES = 16384;
#define NSLOT 12
#define INFLIGHT 3
#define INFLIGHT1 2
#define NFREE 4
#define PACE_T0 2000
#define PACE_DT 650
#define DEEP 7
#define EV_G 2
#define EV_U 4
#define EV_D 4
#define REP3 1
#define PW_IT 0
#define TMPF 0
#define PREWRITE 1
#define BACKOFF 0
#define R_FFN 38
#define FFN_STEP 1
#define P_WO 32
constexpr int NR = NSLOT - 3;
constexpr int NFRONT = 4;
constexpr int NSEQ = NFRONT + 2 * NTILE + 2;
constexpr int NCONS = 256;
constexpr int NTHREADS = NCONS + 32;

__host__ __device__ constexpr int kv2pos(int kv) { return NFRONT + kv + (kv >= P_WO ? 2 : 0); }
__host__ __device__ constexpr int posK(int i) { return kv2pos(i == 0 ? 0 : 2 * i - 1); }
__host__ __device__ constexpr int posV(int i) { return kv2pos(i == NTILE - 1 ? 2 * NTILE - 1 : 2 * i + 2); }
constexpr int POS_WO = NFRONT + P_WO;
constexpr int SL_G = NR, SL_U = NR + 1, SL_D = NR + 2;
static_assert(POS_WO >= NSEQ - NR, "wo must never need to be recycled");
constexpr int NSEQX = R_FFN + 2 * FFN_STEP + 1 > NSEQ ? R_FFN + 2 * FFN_STEP + 1 : NSEQ;

__device__ unsigned g_epoch;
__device__ __align__(128) unsigned g_llmod[6 * NCTA * 16];
__device__ __align__(128) unsigned g_llq[NB * HQ * DH];
__device__ __align__(128) unsigned g_llo[HQ * 16 * DH];
__device__ __align__(128) unsigned g_llml[HQ * 16 * 2];
__device__ __align__(128) unsigned g_ll2[NOWN * HQ * 64];
__device__ __align__(128) unsigned g_ll3[REP3 * NCTA * 16];
__device__ __align__(128) unsigned g_ll4[NOWN * NFFN * 64];
#define STAMP(i)
#define PSTAMP(i)
#define DSTAMP(i, dep)
#define CSTAMP(i)

__device__ __forceinline__ uint32_t smem_u32(const void* p) { return (uint32_t)__cvta_generic_to_shared(p); }
__device__ __forceinline__ uint32_t bfr_hi(float x) {
    uint32_t r; asm("cvt.rn.bf16x2.f32 %0, %1, %2;" : "=r"(r) : "f"(x), "f"(0.f)); return r;
}
__device__ __forceinline__ float bfr(float x) { return __uint_as_float(bfr_hi(x)); }
__device__ __forceinline__ float bf_lo(uint32_t u) { return __uint_as_float(u << 16); }
__device__ __forceinline__ float bf_hi(uint32_t u) { return __uint_as_float(u & 0xffff0000u); }
__device__ __forceinline__ uint32_t pack_bf2(float lo, float hi) {
    uint32_t r; asm("cvt.rn.bf16x2.f32 %0, %1, %2;" : "=r"(r) : "f"(hi), "f"(lo)); return r;
}

__device__ __forceinline__ void mbar_init(uint32_t bar, uint32_t cnt) {
    asm volatile("mbarrier.init.shared::cta.b64 [%0], %1;" :: "r"(bar), "r"(cnt) : "memory");
}
__device__ __forceinline__ void mbar_expect_tx(uint32_t bar, uint32_t bytes) {
    asm volatile("mbarrier.arrive.expect_tx.shared::cta.b64 _, [%0], %1;" :: "r"(bar), "r"(bytes) : "memory");
}
__device__ __forceinline__ void mbar_arrive(uint32_t bar) {
    asm volatile("mbarrier.arrive.shared::cta.b64 _, [%0];" :: "r"(bar) : "memory");
}
__device__ __forceinline__ bool mbar_try(uint32_t bar, uint32_t parity) {
    uint32_t ok;
    asm volatile("{\n\t.reg .pred p;\n\tmbarrier.try_wait.parity.shared::cta.b64 p, [%1], %2;\n\tselp.u32 %0, 1, 0, p;\n\t}"
                 : "=r"(ok) : "r"(bar), "r"(parity) : "memory");
    return ok != 0;
}
__device__ __forceinline__ bool mbar_test(uint32_t bar, uint32_t parity) {
    uint32_t ok;
    asm volatile("{\n\t.reg .pred p;\n\tmbarrier.test_wait.parity.shared::cta.b64 p, [%1], %2;\n\tselp.u32 %0, 1, 0, p;\n\t}"
                 : "=r"(ok) : "r"(bar), "r"(parity) : "memory");
    return ok != 0;
}
__device__ __forceinline__ bool expired(unsigned t0c) { return (unsigned)clock() - t0c > (1u << 24); }
__device__ __forceinline__ void mbar_wait(unsigned t0c, uint32_t bar, uint32_t parity) {
#pragma unroll 1
    while (!mbar_try(bar, parity)) if (expired(t0c)) return;
}
__device__ __forceinline__ void tma2d(uint32_t dst, const CUtensorMap* tm, int c0, int c1, uint32_t bar) {
    asm volatile("cp.async.bulk.tensor.2d.shared::cluster.global.tile.mbarrier::complete_tx::bytes [%0], [%1, {%3, %4}], [%2];"
                 :: "r"(dst), "l"((uint64_t)tm), "r"(bar), "r"(c0), "r"(c1) : "memory");
}
__device__ __forceinline__ void tma3d(uint32_t dst, const CUtensorMap* tm, int c0, int c1, int c2, uint32_t bar) {
    asm volatile("cp.async.bulk.tensor.3d.shared::cluster.global.tile.mbarrier::complete_tx::bytes [%0], [%1, {%3, %4, %5}], [%2];"
                 :: "r"(dst), "l"((uint64_t)tm), "r"(bar), "r"(c0), "r"(c1), "r"(c2) : "memory");
}
__device__ __forceinline__ void tma3d_hint(uint32_t dst, const CUtensorMap* tm, int c0, int c1, int c2, uint32_t bar, uint64_t pol) {
    asm volatile("cp.async.bulk.tensor.3d.shared::cluster.global.tile.mbarrier::complete_tx::bytes.L2::cache_hint [%0], [%1, {%3, %4, %5}], [%2], %6;"
                 :: "r"(dst), "l"((uint64_t)tm), "r"(bar), "r"(c0), "r"(c1), "r"(c2), "l"(pol) : "memory");
}
__device__ __forceinline__ void ldsm4(uint32_t (&r)[4], uint32_t addr) {
    asm volatile("ldmatrix.sync.aligned.m8n8.x4.shared.b16 {%0,%1,%2,%3}, [%4];"
                 : "=r"(r[0]), "=r"(r[1]), "=r"(r[2]), "=r"(r[3]) : "r"(addr) : "memory");
}
__device__ __forceinline__ void ldsm4t(uint32_t (&r)[4], uint32_t addr) {
    asm volatile("ldmatrix.sync.aligned.m8n8.x4.trans.shared.b16 {%0,%1,%2,%3}, [%4];"
                 : "=r"(r[0]), "=r"(r[1]), "=r"(r[2]), "=r"(r[3]) : "r"(addr) : "memory");
}
__device__ __forceinline__ void mma16816(float (&c)[4], const uint32_t (&a)[4], uint32_t b0, uint32_t b1) {
    asm volatile("mma.sync.aligned.m16n8k16.row.col.f32.bf16.bf16.f32 {%0,%1,%2,%3}, {%4,%5,%6,%7}, {%8,%9}, {%0,%1,%2,%3};"
                 : "+f"(c[0]), "+f"(c[1]), "+f"(c[2]), "+f"(c[3])
                 : "r"(a[0]), "r"(a[1]), "r"(a[2]), "r"(a[3]), "r"(b0), "r"(b1));
}
__device__ __forceinline__ uint32_t movm_t(uint32_t a) {
    uint32_t d; asm volatile("movmatrix.sync.aligned.m8n8.trans.b16 %0, %1;" : "=r"(d) : "r"(a)); return d;
}
__device__ __forceinline__ float ex2(float x) {
    float r; asm("ex2.approx.ftz.f32 %0, %1;" : "=f"(r) : "f"(x * 1.4426950408889634f)); return r;
}
__device__ __forceinline__ void cons_sync() { asm volatile("bar.sync 1, 256;" ::: "memory"); }

__device__ __forceinline__ uint4 ld_rlx4(const unsigned* p) {
    uint4 v;
    asm volatile("ld.relaxed.gpu.global.v4.u32 {%0,%1,%2,%3}, [%4];" : "=r"(v.x), "=r"(v.y), "=r"(v.z), "=r"(v.w) : "l"(p) : "memory");
    return v;
}
__device__ __forceinline__ uint2 ld_rlx2(const unsigned* p) {
    uint2 v;
    asm volatile("ld.relaxed.gpu.global.v2.u32 {%0,%1}, [%2];" : "=r"(v.x), "=r"(v.y) : "l"(p) : "memory");
    return v;
}
__device__ __forceinline__ void st_rlx(unsigned* p, unsigned v) {
    asm volatile("st.relaxed.gpu.global.u32 [%0], %1;" :: "l"(p), "r"(v) : "memory");
}
__device__ __forceinline__ void st_rlx2(unsigned* p, unsigned a, unsigned b) {
    asm volatile("st.relaxed.gpu.global.v2.u32 [%0], {%1,%2};" :: "l"(p), "r"(a), "r"(b) : "memory");
}
__device__ __forceinline__ void st_rlx2p(bool pr, unsigned* p, unsigned a, unsigned b) {
    asm volatile("{\n\t.reg .pred p;\n\tsetp.ne.u32 p, %3, 0;\n\t@p st.relaxed.gpu.global.v2.u32 [%0], {%1,%2};\n\t}"
                 :: "l"(p), "r"(a), "r"(b), "r"((unsigned)pr) : "memory");
}
__device__ __forceinline__ bool tag_ok(const uint4& v, unsigned tag, unsigned mask) {
    return (((v.x ^ tag) | (v.y ^ tag) | (v.z ^ tag) | (v.w ^ tag)) & mask) == 0;
}
__device__ __forceinline__ uint4 poll4(unsigned t0c, const unsigned* p, unsigned tag, unsigned mask) {
    uint4 v = ld_rlx4(p);
#pragma unroll 1
    while (!tag_ok(v, tag, mask) && !expired(t0c)) { if (BACKOFF) __nanosleep(BACKOFF); v = ld_rlx4(p); }
    return v;
}
__device__ __forceinline__ void poll4x2(unsigned t0c, const unsigned* p0, const unsigned* p1, unsigned tag, unsigned mask, uint4& a, uint4& b) {
    a = ld_rlx4(p0); b = ld_rlx4(p1);
#pragma unroll 1
    while (true) {
        bool oa = tag_ok(a, tag, mask), ob = tag_ok(b, tag, mask);
        if ((oa && ob) || expired(t0c)) break;
        if (BACKOFF) __nanosleep(BACKOFF);
        if (!oa) a = ld_rlx4(p0);
        if (!ob) b = ld_rlx4(p1);
    }
}
template <int N>
__device__ __forceinline__ void pollN(unsigned t0c, const unsigned* const (&p)[N], unsigned tag, unsigned mask, uint4 (&v)[N]) {
#pragma unroll
    for (int i = 0; i < N; i++) v[i] = ld_rlx4(p[i]);
#pragma unroll 1
    while (true) {
        bool all = true;
#pragma unroll
        for (int i = 0; i < N; i++) if (!tag_ok(v[i], tag, mask)) { all = false; v[i] = ld_rlx4(p[i]); }
        if (all || expired(t0c)) break;
    }
}
__device__ __forceinline__ unsigned tagf(float v, unsigned tag4) { return (__float_as_uint(v) & ~0xFu) | tag4; }
__device__ __forceinline__ float untagf(unsigned u) { return __uint_as_float(u); }
__device__ __forceinline__ float owner_reduce(float v0, float v1, float v2, float v3, float* red) {
    const int tid = threadIdx.x, lane = tid & 31;
    const bool h = lane & 16;
    const float k0 = (h ? v2 : v0) + __shfl_xor_sync(0xffffffffu, h ? v0 : v2, 16);
    const float k1 = (h ? v3 : v1) + __shfl_xor_sync(0xffffffffu, h ? v1 : v3, 16);
    *(float2*)(red + (tid >> 5) * 64 + (lane & 15) * 4 + (h ? 2 : 0)) = make_float2(k0, k1);
    cons_sync();
    const float* p = red + (tid & 63);
    return ((p[0] + p[64]) + (p[128] + p[192])) + ((p[256] + p[320]) + (p[384] + p[448]));
}

constexpr int SM_RING = 0;
constexpr int SM_MISC = NSLOT * SLOT_BYTES;
constexpr int ACT_PITCH = 520;
constexpr int SM_OBUF  = SM_MISC;
constexpr int OB_HP = 136, OB_WP = 4 * OB_HP;
constexpr int SM_ACT   = SM_OBUF + 8 * OB_WP * 4;
constexpr int SM_QS    = SM_ACT + 4 * ACT_PITCH * 2;
constexpr int SM_RED   = SM_QS + 4 * 136 * 2;
constexpr int SM_ML    = SM_RED + (512 + 64 + 512) * 4;
constexpr int SM_ST    = SM_ML + 8 * 4 * 2 * 4;
constexpr int SM_BAR   = SM_ST + 64 * 4;
constexpr int SM_TOTAL = SM_BAR + 2 * NSLOT * 8 + 32;
static_assert(SM_TOTAL <= 232448, "smem");

__device__ __noinline__ float gemv32(uint32_t a0, uint32_t a1, uint32_t ks_stride, const bf16* act_s, float* obuf) {
    const int tid = threadIdx.x, warp = tid >> 5, lane = tid & 31, g = lane >> 2, t = lane & 3;
    float acc[2][4] = {};
#pragma unroll
    for (int ks = 0; ks < 4; ks++) {
        const int k0 = warp * 64 + ks * 16;
        uint32_t b0 = 0, b1 = 0;
        if (g < 4) {
            b0 = *(const uint32_t*)(act_s + g * ACT_PITCH + k0 + 2 * t);
            b1 = *(const uint32_t*)(act_s + g * ACT_PITCH + k0 + 2 * t + 8);
        }
        uint32_t a[4], a2[4];
        ldsm4t(a, a0 + ks * ks_stride);
        ldsm4t(a2, a1 + ks * ks_stride);
        mma16816(acc[0], a, b0, b1);
        mma16816(acc[1], a2, b0, b1);
    }
    if (t < 2) {
#pragma unroll
        for (int mt = 0; mt < 2; mt++) {
            obuf[warp * 128 + (2 * t) * 32 + mt * 16 + g] = acc[mt][0];
            obuf[warp * 128 + (2 * t + 1) * 32 + mt * 16 + g] = acc[mt][1];
            obuf[warp * 128 + (2 * t) * 32 + mt * 16 + g + 8] = acc[mt][2];
            obuf[warp * 128 + (2 * t + 1) * 32 + mt * 16 + g + 8] = acc[mt][3];
        }
    }
    cons_sync();
    float s = 0.f;
    if (tid < 128) {
        const float* p = obuf + tid;
        s = ((p[0] + p[128]) + (p[256] + p[384])) + ((p[512] + p[640]) + (p[768] + p[896]));
    }
    return s;
}
__device__ __forceinline__ uint32_t pk_lo(const uint4& a) { return (a.x >> 16) | (a.y & 0xffff0000u); }
__device__ __forceinline__ uint32_t pk_hi(const uint4& a) { return (a.z >> 16) | (a.w & 0xffff0000u); }

__device__ __forceinline__ void
fused_body(const CUtensorMap& tmK, const CUtensorMap& tmV, const CUtensorMap& tmWq, const CUtensorMap& tmWo,
           const CUtensorMap& tmWg, const CUtensorMap& tmWu, const CUtensorMap& tmWd, const CUtensorMap& tmWm,
           const bf16* __restrict__ x, const bf16* __restrict__ cvec, bf16* __restrict__ out
           )
{
    extern __shared__ __align__(1024) uint8_t smem[];
    const uint32_t sbase = smem_u32(smem);
    const int tid = threadIdx.x, warp = tid >> 5, lane = tid & 31;
    const unsigned t0c = (unsigned)clock();
    const int j = blockIdx.x;
    const int ab = j >> 5, ag = (j >> 2) & 7, as = j & 3;
    const uint32_t bar_full = sbase + SM_BAR, bar_empty = bar_full + NSLOT * 8;
    const uint32_t bar_qdone = bar_empty + NSLOT * 8, bar_t1 = bar_qdone + 8;
    const int modG = j < 64 ? j : 2 * j - 64;

    if (warp == 8) {
        if (lane == 0) {
            PSTAMP(16);
            if (sbase & 1023u) __trap();
            for (int s = 0; s < NSLOT; s++) { mbar_init(bar_full + s * 8, 1); mbar_init(bar_empty + s * 8, 4); }
            mbar_init(bar_qdone, 1); mbar_init(bar_t1, 1); mbar_init(bar_t1 + 8, 1);
            asm volatile("fence.mbarrier_init.release.cluster;" ::: "memory");
            asm volatile("fence.proxy.async.shared::cta;" ::: "memory");
        }
        __syncwarp();
        asm volatile("bar.arrive 2, 288;" ::: "memory");
        if (lane == 0) {
            uint64_t pol;
            asm volatile("createpolicy.fractional.L2::evict_first.b64 %0, 1.0;" : "=l"(pol));
            const int row0 = (ab * HKV + ag) * SK + (SK - WIN) + as * KEYS_PER_CTA;
            int kv = 0;
            bool qdone = false;
            unsigned tg0; asm volatile("mov.u32 %0, %globaltimer_lo;" : "=r"(tg0));
#pragma unroll 1
            for (int pos = 0; pos < NSEQX; pos++) {
                const int slot = pos % NR, use = pos / NR;
                const uint32_t dst = sbase + SM_RING + slot * SLOT_BYTES, fb = bar_full + slot * 8;
                if (pos == 1 && j < 64) { mbar_arrive(fb); continue; }
                if (!qdone) qdone = mbar_test(bar_qdone, 0);
                int depth = qdone ? INFLIGHT : INFLIGHT1;
                if (DEEP != INFLIGHT && qdone) {
                    unsigned now; asm volatile("mov.u32 %0, %globaltimer_lo;" : "=r"(now));
                    if ((int)(now - tg0) > PACE_T0 + (pos - NFRONT) * PACE_DT) depth = DEEP;
                }
                if (pos >= NFREE && depth < NR && pos - depth < NSEQ) {
                    const int p2 = pos - depth;
                    mbar_wait(t0c, bar_full + (p2 % NR) * 8, (p2 / NR) & 1);
                }
                if (j < NFFN && pos >= R_FFN && pos <= R_FFN + 2 * FFN_STEP && (pos - R_FFN) % FFN_STEP == 0) {
                    const int f = (pos - R_FFN) / FFN_STEP;
                    const uint32_t d2 = sbase + SM_RING + (NR + f) * SLOT_BYTES, f2 = bar_full + (NR + f) * 8;
                    const int ev = f == 0 ? EV_G : f == 1 ? EV_U : EV_D;
                    if (ev & 3) mbar_wait(t0c, bar_t1 + ((ev & 3) - 1) * 8, 0);
                    if (ev & 4) mbar_wait(t0c, f2 - 8, 0);
                    mbar_expect_tx(f2, SLOT_BYTES);
                    if (f < 2) {
                        tma2d(d2, f ? &tmWu : &tmWg, 16 * j, 0, f2);
                        tma2d(d2 + 8192, f ? &tmWu : &tmWg, 16 * j, 256, f2);
                    } else {
                        tma3d(d2, &tmWd, 0, 16 * j, 0, f2);
                    }
                }
                if (pos >= NSEQ) continue;
                if (use > 0) mbar_wait(t0c, bar_empty + slot * 8, (use - 1) & 1);
                mbar_expect_tx(fb, SLOT_BYTES);
                if (pos < 2) {
                    tma2d(dst, &tmWm, 16 * (modG + pos), 0, fb);
                    tma2d(dst + 8192, &tmWm, 16 * (modG + pos), 256, fb);
                } else if (pos < 4) {
                    tma2d(dst, &tmWq, 32 * j, 256 * (pos - 2), fb);
                } else if (pos == POS_WO || pos == POS_WO + 1) {
                    tma2d(dst, &tmWo, 128 * (j & 3) + 64 * (pos - POS_WO), 128 * (j >> 2), fb);
                } else {
                    const bool isK = (kv == 0) || ((kv & 1) && kv < 2 * NTILE - 1);
                    const int ti = isK ? ((kv + 1) >> 1) : (kv == 2 * NTILE - 1 ? NTILE - 1 : (kv >> 1) - 1);
                    tma3d_hint(dst, isK ? &tmK : &tmV, 0, row0 + ti * TILE_KEYS, 0, fb, pol);
                    kv++;
                }
                if (pos == 3) PSTAMP(24);
                if (pos == 6) PSTAMP(25);
                if (pos == 10) PSTAMP(26);
                if (pos == 14) PSTAMP(27);
            }
            PSTAMP(17);
        }
        return;
    }

    STAMP(0);
    float* obuf = (float*)(smem + SM_OBUF);
    bf16* act_s = (bf16*)(smem + SM_ACT);
    bf16* qs = (bf16*)(smem + SM_QS);
    float* red = (float*)(smem + SM_RED);
    float* mls = (float*)(smem + SM_ML);
    float* st = (float*)(smem + SM_ST);
    const int g = lane >> 2, t = lane & 3;
    const int mi = lane >> 3, lr = lane & 7;
    const int ub = tid & 3, uj = tid >> 2;

    unsigned epoch;
    asm volatile("ld.relaxed.gpu.global.u32 %0, [%1];" : "=r"(epoch) : "l"(&g_epoch) : "memory");
    const uint2 cu0 = __ldg((const uint2*)(cvec + ub * DM + 4 * uj)), cu1 = __ldg((const uint2*)(cvec + ub * DM + 4 * (uj + 64)));
    const uint2 xu0 = __ldg((const uint2*)(x + ub * DM + 4 * uj)), xu1 = __ldg((const uint2*)(x + ub * DM + 4 * (uj + 64)));
    const bool owner = (j & 3) == 0;
    const int oc = 4 * j + ((tid & 63) >> 2);
    float xown = 0.f;
    if (owner) xown = __bfloat162float(x[(tid & 3) * DM + oc]);
    unsigned* const mod_dst = &g_llmod[(modG * 4 + ((tid & 31) >> 2)) * 16 + (tid >> 5) * 4 + (tid & 3)];
    unsigned* const q_dst = &g_llq[(tid >> 5) * (HQ * DH) + 32 * j + (tid & 31)];
    const bool mod_pub = tid < 128 && (j >= 64 || (tid & 31) < 16);
    unsigned* const o_dst = &g_llo[((ag * 4 + (tid >> 6)) * 16 + ab * 4 + as) * DH + (tid & 63) * 2];
    unsigned* const ml_dst = &g_llml[((ag * 4 + (tid >> 6)) * 16 + ab * 4 + as) * 2];
    unsigned* const p2_dst = &g_ll2[(((j & 3) * 8 + warp) * HQ + (j >> 2)) * 64 + g * 4 + 2 * t];
    unsigned* const p4_dst = &g_ll4[(warp * 4 * NFFN + j) * 64 + g * 4 + 2 * t];
    unsigned* const x1_dst = &g_ll3[(tid >> 6) * (NCTA * 16) + (oc >> 2) * 16 + (tid & 3) * 4 + (oc & 3)];
    auto reset_tail = [&]() {
        st_rlx2(o_dst, 0u, 0u);
        st_rlx2p((tid & 63) == 0, ml_dst, 0u, 0u);
        st_rlx2p(t < 2, p2_dst, 0u, 0u);
        st_rlx2p(t < 2, p2_dst + 32, 0u, 0u);
#pragma unroll
        for (int i = 0; i < 8; i++) st_rlx2p(t < 2 && j < NFFN, p4_dst + (i >> 1) * (NFFN * 64) + (i & 1) * 32, 0u, 0u);
        if (owner && tid < 64 * REP3) st_rlx(x1_dst, 0u);
    };
    if (mod_pub) st_rlx(mod_dst, 0u);
    if (tid < 128) st_rlx(q_dst, 0u);
    if (warp < 4) {
        const uint4* xp = (const uint4*)(x + warp * DM);
        uint4 u0 = __ldg(xp + lane), u1 = __ldg(xp + 32 + lane);
        uint32_t w[8] = {u0.x, u0.y, u0.z, u0.w, u1.x, u1.y, u1.z, u1.w};
        float s = 0.f;
#pragma unroll
        for (int i = 0; i < 8; i++) s += bf_lo(w[i]) + bf_hi(w[i]);
#pragma unroll
        for (int o = 16; o; o >>= 1) s += __shfl_xor_sync(0xffffffffu, s, o);
        const float mean = s * (1.f / DM);
        float q = 0.f;
#pragma unroll
        for (int i = 0; i < 8; i++) { float a = bf_lo(w[i]) - mean, b2 = bf_hi(w[i]) - mean; q += a * a + b2 * b2; }
#pragma unroll
        for (int o = 16; o; o >>= 1) q += __shfl_xor_sync(0xffffffffu, q, o);
        if (lane == 0) {
            st[warp] = bfr(mean);
            st[4 + warp] = __frcp_rn(bfr(__fsqrt_rn(bfr(bfr(q * (1.f / DM)) + 1e-5f))));
        }
    }
    {
        auto silu2 = [](uint32_t u) {
            const float a = bf_lo(u), b = bf_hi(u);
            return pack_bf2(__fdividef(a, 1.f + __expf(-a)), __fdividef(b, 1.f + __expf(-b)));
        };
        *(uint2*)(act_s + ub * ACT_PITCH + 4 * uj) = make_uint2(silu2(cu0.x), silu2(cu0.y));
        *(uint2*)(act_s + ub * ACT_PITCH + 4 * (uj + 64)) = make_uint2(silu2(cu1.x), silu2(cu1.y));
    }
    const unsigned tag16 = 1u + epoch % 65535u, tag4 = 1u + epoch % 15u;
    asm volatile("bar.sync 2, 288;" ::: "memory");
    STAMP(18);

    const uint32_t off32 = (uint32_t)((warp * 64 + lr + (mi >> 1) * 8) * 32 + (((mi & 1) ^ ((lr >> 2) & 1)) << 4));
    {
        mbar_wait(t0c, bar_full, 0);
        if (j >= 64) mbar_wait(t0c, bar_full + 8, 0);
        STAMP(19);
        const float s = gemv32(sbase + SM_RING + off32, sbase + SM_RING + SLOT_BYTES + off32, 512, act_s, obuf);
        if (mod_pub) st_rlx(mod_dst, bfr_hi(s) | tag16);
        if (tid < 128 && lane == 0) { mbar_arrive(bar_empty); mbar_arrive(bar_empty + 8); }
    }
    STAMP(1);
    {
        const float mu = st[ub], sd = st[4 + ub];
#pragma unroll
        for (int i = 0; i < 2; i++) {
            uint4 a, b;
            poll4x2(t0c, &g_llmod[(uj + 64 * i) * 16 + ub * 4], &g_llmod[NCTA * 16 + (uj + 64 * i) * 16 + ub * 4], tag16, 0xffffu, a, b);
            const uint2 xu = i ? xu1 : xu0;
            const float h0 = bfr(bfr(bfr(bf_lo(xu.x) - mu) * sd) * bfr(1.f + bf_hi(b.x))) + bf_hi(a.x);
            const float h1 = bfr(bfr(bfr(bf_hi(xu.x) - mu) * sd) * bfr(1.f + bf_hi(b.y))) + bf_hi(a.y);
            const float h2 = bfr(bfr(bfr(bf_lo(xu.y) - mu) * sd) * bfr(1.f + bf_hi(b.z))) + bf_hi(a.z);
            const float h3 = bfr(bfr(bfr(bf_hi(xu.y) - mu) * sd) * bfr(1.f + bf_hi(b.w))) + bf_hi(a.w);
            *(uint2*)(act_s + ub * ACT_PITCH + 4 * (uj + 64 * i)) = make_uint2(pack_bf2(h0, h1), pack_bf2(h2, h3));
        }
    }
    mbar_wait(t0c, bar_full + (2 + (warp >> 2)) * 8, 0);
    cons_sync();
    STAMP(2);
    {
        const int row = (warp & 3) * 64 + lr + (mi >> 1) * 8;
        const uint32_t base = sbase + SM_RING + (2 + (warp >> 2)) * SLOT_BYTES + row * 64;
        const int sw = (row >> 1) & 3;
        const float s = gemv32(base + (((mi & 1) ^ sw) << 4), base + (((2 + (mi & 1)) ^ sw) << 4), 1024, act_s, obuf);
        if (tid < 128) {
            st_rlx(q_dst, bfr_hi(s) | tag16);
            if (lane == 0) { mbar_arrive(bar_empty + 16); mbar_arrive(bar_empty + 24); }
        }
    }
    STAMP(3);
    uint32_t sbp[2][2], cbp[2][2];
    float gav = 0.f, gbv = 0.f;
#pragma unroll
    for (int i = 0; i < 2; i++) {
        uint4 a, b;
        poll4x2(t0c, &g_llmod[3 * NCTA * 16 + (uj + 64 * i) * 16 + ub * 4], &g_llmod[4 * NCTA * 16 + (uj + 64 * i) * 16 + ub * 4], tag16, 0xffffu, a, b);
        sbp[i][0] = pk_lo(a); sbp[i][1] = pk_hi(a);
        cbp[i][0] = pack_bf2(1.f + bf_hi(b.x), 1.f + bf_hi(b.y)); cbp[i][1] = pack_bf2(1.f + bf_hi(b.z), 1.f + bf_hi(b.w));
    }
    if (owner) {
        uint4 a, b;
        poll4x2(t0c, &g_llmod[2 * NCTA * 16 + (oc >> 2) * 16 + (tid & 3) * 4], &g_llmod[5 * NCTA * 16 + (oc >> 2) * 16 + (tid & 3) * 4], tag16, 0xffffu, a, b);
        const int c = oc & 3;
        gav = bf_hi(c == 0 ? a.x : c == 1 ? a.y : c == 2 ? a.z : a.w);
        gbv = bf_hi(c == 0 ? b.x : c == 1 ? b.y : c == 2 ? b.z : b.w);
    }
    if (tid >= 128) {
        const int u = tid - 128;
        uint4 a = poll4(t0c, &g_llq[ab * (HQ * DH) + ag * 512 + u * 4], tag16, 0xffffu);
        *(uint2*)(qs + (u >> 5) * 136 + (u & 31) * 4) = make_uint2(pk_lo(a), pk_hi(a));
    }
    cons_sync();
    if (tid == 32) mbar_arrive(bar_qdone);
    uint32_t qf[8][2];
#pragma unroll
    for (int ks = 0; ks < 8; ks++) {
        qf[ks][0] = 0; qf[ks][1] = 0;
        if (g < 4) {
            qf[ks][0] = *(const uint32_t*)(qs + g * 136 + ks * 16 + 2 * t);
            qf[ks][1] = *(const uint32_t*)(qs + g * 136 + ks * 16 + 2 * t + 8);
        }
    }
    STAMP(4);

    float o[8][4];
#pragma unroll
    for (int i = 0; i < 8; i++) { o[i][0] = o[i][1] = o[i][2] = o[i][3] = 0.f; }
    float m0 = -INFINITY, m1 = -INFINITY, l0 = 0.f, l1 = 0.f;

    {
        const int w4 = warp & 3, grp = warp >> 2;
        const int keyK = w4 * 16 + lr + (mi & 1) * 8, chK = mi >> 1;
        const int keyV = w4 * 16 + lr + (mi >> 1) * 8, chV = mi & 1;
        const uint32_t offK = keyK * 128, offV = keyV * 128;
#pragma unroll 1
        for (int it = 0; it < NTILE / 2; it++) {
            const int ti = 2 * it + grp;
            if (it == PW_IT) reset_tail();
            const int pk = posK(ti), pv = posV(ti);
            const int sk = pk % NR, sv = pv % NR;
            mbar_wait(t0c, bar_full + sk * 8, (pk / NR) & 1);
            float s0[4] = {0.f, 0.f, 0.f, 0.f}, s1[4] = {0.f, 0.f, 0.f, 0.f};
            const uint32_t kb = sbase + SM_RING + sk * SLOT_BYTES + offK;
#pragma unroll
            for (int ks = 0; ks < 4; ks++) {
                uint32_t a[4], a2[4];
                const uint32_t sw = (uint32_t)(((2 * ks + chK) ^ lr) << 4);
                ldsm4(a, kb + sw);
                ldsm4(a2, kb + 8192 + sw);
                mma16816(s0, a, qf[ks][0], qf[ks][1]);
                mma16816(s1, a2, qf[4 + ks][0], qf[4 + ks][1]);
            }
            __syncwarp();
            if (lane == 0) mbar_arrive(bar_empty + sk * 8);
            float sv4[4];
#pragma unroll
            for (int i = 0; i < 4; i++) sv4[i] = bfr(bfr(s0[i] + s1[i]) * 0.08838834764831845f);
            float x0 = fmaxf(sv4[0], sv4[2]), x1 = fmaxf(sv4[1], sv4[3]);
#pragma unroll
            for (int off = 4; off < 32; off <<= 1) {
                x0 = fmaxf(x0, __shfl_xor_sync(0xffffffffu, x0, off));
                x1 = fmaxf(x1, __shfl_xor_sync(0xffffffffu, x1, off));
            }
            const float n0 = fmaxf(m0, x0), n1 = fmaxf(m1, x1);
            if (__any_sync(0xffffffffu, n0 > m0 || n1 > m1)) {
                const float f0 = ex2(m0 - n0), f1 = ex2(m1 - n1);
                l0 *= f0; l1 *= f1;
#pragma unroll
                for (int i = 0; i < 8; i++) { o[i][0] *= f0; o[i][1] *= f1; o[i][2] *= f0; o[i][3] *= f1; }
                m0 = n0; m1 = n1;
            }
            const float p0 = ex2(sv4[0] - m0), p1 = ex2(sv4[1] - m1);
            const float p2 = ex2(sv4[2] - m0), p3 = ex2(sv4[3] - m1);
            l0 += p0 + p2; l1 += p1 + p3;
            const uint32_t pb0 = movm_t(pack_bf2(p0, p1)), pb1 = movm_t(pack_bf2(p2, p3));
            mbar_wait(t0c, bar_full + sv * 8, (pv / NR) & 1);
            const uint32_t vb = sbase + SM_RING + sv * SLOT_BYTES + offV;
#pragma unroll
            for (int mt = 0; mt < 8; mt++) {
                uint32_t a[4];
                ldsm4t(a, vb + (mt >> 2) * 8192 + (uint32_t)(((2 * (mt & 3) + chV) ^ lr) << 4));
                mma16816(o[mt], a, pb0, pb1);
            }
            __syncwarp();
            if (lane == 0) mbar_arrive(bar_empty + sv * 8);
        }
    }
    STAMP(5);
    {
        float la = l0, lb = l1;
#pragma unroll
        for (int off = 4; off < 32; off <<= 1) {
            la += __shfl_xor_sync(0xffffffffu, la, off);
            lb += __shfl_xor_sync(0xffffffffu, lb, off);
        }
        if (t < 2) {
            if (g == 0) {
                *(float2*)(mls + (2 * t) * 16 + warp * 2) = make_float2(m0, la);
                *(float2*)(mls + (2 * t + 1) * 16 + warp * 2) = make_float2(m1, lb);
            }
            float* ob = obuf + warp * OB_WP + 2 * t * OB_HP + g;
#pragma unroll
            for (int mt = 0; mt < 8; mt++) {
                ob[mt * 16] = o[mt][0]; ob[OB_HP + mt * 16] = o[mt][1];
                ob[mt * 16 + 8] = o[mt][2]; ob[OB_HP + mt * 16 + 8] = o[mt][3];
            }
        }
        cons_sync();
        const int hd = tid >> 6, d = (tid & 63) * 2;
        float4 ml4[4];
#pragma unroll
        for (int w = 0; w < 4; w++) ml4[w] = *(const float4*)(mls + hd * 16 + w * 4);
        const float M = untagf(tagf(fmaxf(fmaxf(fmaxf(ml4[0].x, ml4[0].z), fmaxf(ml4[1].x, ml4[1].z)), fmaxf(fmaxf(ml4[2].x, ml4[2].z), fmaxf(ml4[3].x, ml4[3].z))), tag4));
        float a0 = 0.f, a1 = 0.f, L = 0.f;
#pragma unroll
        for (int w = 0; w < 8; w++) {
            const float f = ex2(((w & 1) ? ml4[w >> 1].z : ml4[w >> 1].x) - M);
            const float2 v = *(const float2*)(obuf + w * OB_WP + hd * OB_HP + d);
            a0 += f * v.x; a1 += f * v.y;
            L += f * ((w & 1) ? ml4[w >> 1].w : ml4[w >> 1].y);
        }
        st_rlx2(o_dst, tagf(a0, tag4), tagf(a1, tag4));
        st_rlx2p((tid & 63) == 0, ml_dst, tagf(M, tag4), tagf(L, tag4));
    }

    if (tid == 32) mbar_arrive(bar_t1);
    STAMP(6);
    {
        mbar_wait(t0c, bar_full + ((POS_WO + (warp >> 2)) % NR) * 8, ((POS_WO + (warp >> 2)) / NR) & 1);
        const uint32_t base = sbase + SM_RING + ((POS_WO + (warp >> 2)) % NR) * SLOT_BYTES + (lr + (mi >> 1) * 8) * 128 +
                              (((2 * (warp & 3) + (mi & 1)) ^ lr) << 4);
        uint32_t wf[8][4];
#pragma unroll
        for (int ks = 0; ks < 8; ks++) ldsm4t(wf[ks], base + ks * 2048);
        {
            const int b = tid >> 6, u = (tid & 63) >> 1, sp = tid & 1;
            const unsigned* seg = &g_llo[((j >> 2) * 16 + b * 4 + 2 * sp) * DH + 4 * u];
            const unsigned* const pp[3] = {seg, seg + DH, &g_llml[((j >> 2) * 16 + b * 4 + 2 * sp) * 2]};
            uint4 v[3];
            pollN<3>(t0c, pp, tag4, 0xfu, v);
            const float ma = untagf(v[2].x), mb = untagf(v[2].z);
            float M = fmaxf(ma, mb);
            M = fmaxf(M, __shfl_xor_sync(0xffffffffu, M, 1));
            const float ea = ex2(ma - M), eb = ex2(mb - M);
            float L = ea * untagf(v[2].y) + eb * untagf(v[2].w);
            const float w0 = ea * untagf(v[0].x) + eb * untagf(v[1].x), w1 = ea * untagf(v[0].y) + eb * untagf(v[1].y);
            const float w2 = ea * untagf(v[0].z) + eb * untagf(v[1].z), w3 = ea * untagf(v[0].w) + eb * untagf(v[1].w);
            L += __shfl_xor_sync(0xffffffffu, L, 1);
            const float k0 = (sp ? w2 : w0) + __shfl_xor_sync(0xffffffffu, sp ? w0 : w2, 1);
            const float k1 = (sp ? w3 : w1) + __shfl_xor_sync(0xffffffffu, sp ? w1 : w3, 1);
            const float r = __fdividef(1.f, L);
            *(uint32_t*)(qs + b * 136 + 4 * u + 2 * sp) = pack_bf2(k0 * r, k1 * r);
        }
        cons_sync();

        if (tid == 32) mbar_arrive(bar_t1 + 8);
        STAMP(7);
        float acc[2][4] = {};
#pragma unroll
        for (int ks = 0; ks < 8; ks++) {
            uint32_t b0 = 0, b1 = 0;
            if (g < 4) {
                b0 = *(const uint32_t*)(qs + g * 136 + ks * 16 + 2 * t);
                b1 = *(const uint32_t*)(qs + g * 136 + ks * 16 + 2 * t + 8);
            }
            mma16816(acc[ks & 1], wf[ks], b0, b1);
        }
        st_rlx2p(t < 2, p2_dst, tagf(acc[0][0] + acc[1][0], tag4), tagf(acc[0][1] + acc[1][1], tag4));
        st_rlx2p(t < 2, p2_dst + 32, tagf(acc[0][2] + acc[1][2], tag4), tagf(acc[0][3] + acc[1][3], tag4));
    }
    STAMP(8);
    float x1own = 0.f;
    if (owner) {
        uint4 a, b;
        const unsigned* p = &g_ll2[(j >> 2) * (HQ * 64) + tid * 4];
        poll4x2(t0c, p, p + 1024, tag4, 0xfu, a, b);
        const float s = owner_reduce(untagf(a.x) + untagf(b.x), untagf(a.y) + untagf(b.y), untagf(a.z) + untagf(b.z), untagf(a.w) + untagf(b.w), red);
        x1own = bfr(xown + bfr(gav * bfr(s)));
        if (tid < 64 * REP3) st_rlx(x1_dst, __float_as_uint(x1own) | tag16);
    }
    STAMP(9);
    if (j < NFFN) {
        uint4 a, b;
        poll4x2(t0c, &g_ll3[(j % REP3) * (NCTA * 16) + tid * 4], &g_ll3[(j % REP3) * (NCTA * 16) + (tid + 256) * 4], tag16, 0xffffu, a, b);
        STAMP(14);
        CSTAMP(1);
        float xv[8] = {bf_hi(a.x), bf_hi(a.y), bf_hi(a.z), bf_hi(a.w), bf_hi(b.x), bf_hi(b.y), bf_hi(b.z), bf_hi(b.w)};
        float mean = (((xv[0] + xv[1]) + (xv[2] + xv[3])) + ((xv[4] + xv[5]) + (xv[6] + xv[7]))) * 0.125f;
        float m2 = 0.f, m2b = 0.f;
#pragma unroll
        for (int i = 0; i < 4; i++) { m2 += (xv[i] - mean) * (xv[i] - mean); m2b += (xv[4 + i] - mean) * (xv[4 + i] - mean); }
        m2 += m2b;
        float n = 8.f;
#pragma unroll
        for (int off = 4; off < 32; off <<= 1) {
            const float om = __shfl_xor_sync(0xffffffffu, mean, off), o2 = __shfl_xor_sync(0xffffffffu, m2, off);
            const float dlt = om - mean;
            m2 = m2 + o2 + dlt * dlt * (n * 0.5f);
            mean = 0.5f * (mean + om);
            n *= 2.f;
        }
        if (lane < 4) { red[512 + lane * 16 + warp] = mean; red[512 + lane * 16 + 8 + warp] = m2; }
        CSTAMP(2);
        cons_sync();
        CSTAMP(3);
        const float4 a0 = *(const float4*)(red + 512 + ub * 16), a1 = *(const float4*)(red + 512 + ub * 16 + 4);
        const float4 q0 = *(const float4*)(red + 512 + ub * 16 + 8), q1 = *(const float4*)(red + 512 + ub * 16 + 12);
        const float mu = (((a0.x + a0.y) + (a0.z + a0.w)) + ((a1.x + a1.y) + (a1.z + a1.w))) * 0.125f;
        auto sq = [mu](float v) { return (v - mu) * (v - mu); };
        const float M2 = (((q0.x + q0.y) + (q0.z + q0.w)) + ((q1.x + q1.y) + (q1.z + q1.w))) +
                         64.f * (((sq(a0.x) + sq(a0.y)) + (sq(a0.z) + sq(a0.w))) + ((sq(a1.x) + sq(a1.y)) + (sq(a1.z) + sq(a1.w))));
        float sq_; asm("sqrt.approx.f32 %0, %1;" : "=f"(sq_) : "f"(bfr(bfr(M2 * (1.f / DM)) + 1e-5f)));
        const float mub = bfr(mu), sd = __fdividef(1.f, bfr(sq_));
#pragma unroll
        for (int i = 0; i < 2; i++) {
            float hv[4];
#pragma unroll
            for (int c = 0; c < 4; c++) {
                const uint32_t sw = sbp[i][c >> 1], cw = cbp[i][c >> 1];
                const float sbv = (c & 1) ? bf_hi(sw) : bf_lo(sw), cbv = (c & 1) ? bf_hi(cw) : bf_lo(cw);
                hv[c] = bfr(bfr(bfr(xv[i * 4 + c] - mub) * sd) * cbv) + sbv;
            }
            *(uint2*)(act_s + ub * ACT_PITCH + 4 * (uj + 64 * i)) = make_uint2(pack_bf2(hv[0], hv[1]), pack_bf2(hv[2], hv[3]));
        }
        CSTAMP(4);
        mbar_wait(t0c, bar_full + SL_G * 8, 0);
        mbar_wait(t0c, bar_full + SL_U * 8, 0);
        cons_sync();
        STAMP(10);
        CSTAMP(5);
        uint32_t af[4][4];
        {
            float gs = gemv32(sbase + SM_RING + SL_G * SLOT_BYTES + off32,
                              sbase + SM_RING + SL_U * SLOT_BYTES + off32, 512, act_s, obuf);
            if (tid < 128) {
                gs = bfr(gs);
                const float us = __shfl_xor_sync(0xffffffffu, gs, 16);
                const float inner = 0.7978845608028654f * (gs + 0.044715f * gs * gs * gs);
                const float ge = bfr(__fdividef(gs, 1.f + ex2(-2.f * inner)));
                if (lane < 16) ((unsigned short*)qs)[warp * 136 + lane] = (unsigned short)(bfr_hi(ge * us) >> 16);
            }
            mbar_wait(t0c, bar_full + SL_D * 8, 0);
            const uint32_t base = sbase + SM_RING + SL_D * SLOT_BYTES + warp * 2048 + (lr + (mi >> 1) * 8) * 128;
#pragma unroll
            for (int mt = 0; mt < 4; mt++) ldsm4t(af[mt], base + (((2 * mt + (mi & 1)) ^ lr) << 4));
            cons_sync();
        }
        STAMP(11);
        CSTAMP(6);
        {
            uint32_t b0 = 0, b1 = 0;
            if (g < 4) {
                b0 = *(const uint32_t*)(qs + g * 136 + 2 * t);
                b1 = *(const uint32_t*)(qs + g * 136 + 2 * t + 8);
            }
            float acc[4][4] = {};
#pragma unroll
            for (int mt = 0; mt < 4; mt++) mma16816(acc[mt], af[mt], b0, b1);
#pragma unroll
            for (int mt = 0; mt < 4; mt++) {
                st_rlx2p(t < 2, p4_dst + mt * (NFFN * 64), tagf(acc[mt][0], tag4), tagf(acc[mt][1], tag4));
                st_rlx2p(t < 2, p4_dst + mt * (NFFN * 64) + 32, tagf(acc[mt][2], tag4), tagf(acc[mt][3], tag4));
            }
        }
    }
    STAMP(12);
    CSTAMP(7);
    if (owner) {
        const unsigned* p = &g_ll4[(j >> 2) * (NFFN * 64) + tid * 4];
        const unsigned* const pp[7] = {p, p + 1024, p + 2048, p + 3072, p + 4096, p + 5120, p + 6144};
        uint4 v[7];
        pollN<7>(t0c, pp, tag4, 0xfu, v);
#define SUM7(c) (((untagf(v[0].c) + untagf(v[1].c)) + (untagf(v[2].c) + untagf(v[3].c))) + ((untagf(v[4].c) + untagf(v[5].c)) + untagf(v[6].c)))
        const float s = owner_reduce(SUM7(x), SUM7(y), SUM7(z), SUM7(w), red + 576);
        if (tid < 64) ((unsigned short*)out)[(tid & 3) * DM + oc] = (unsigned short)(bfr_hi(x1own + bfr(gbv * bfr(s))) >> 16);
        if (j == 0 && tid == 0) st_rlx(&g_epoch, epoch + 1);
    }
    STAMP(13);
    CSTAMP(0);
}

__global__ void __launch_bounds__(NTHREADS, 1)
fused_kernel(const __grid_constant__ CUtensorMap tmK, const __grid_constant__ CUtensorMap tmV,
             const __grid_constant__ CUtensorMap tmWq, const __grid_constant__ CUtensorMap tmWo,
             const __grid_constant__ CUtensorMap tmWg, const __grid_constant__ CUtensorMap tmWu,
             const __grid_constant__ CUtensorMap tmWd, const __grid_constant__ CUtensorMap tmWm,
             const bf16* __restrict__ x, const bf16* __restrict__ cvec, bf16* __restrict__ out)
{
    fused_body(tmK, tmV, tmWq, tmWo, tmWg, tmWu, tmWd, tmWm, x, cvec, out);
}

typedef CUresult (*EncodeFn)(CUtensorMap*, CUtensorMapDataType, cuuint32_t, void*, const cuuint64_t*, const cuuint64_t*,
                             const cuuint32_t*, const cuuint32_t*, CUtensorMapInterleave, CUtensorMapSwizzle,
                             CUtensorMapL2promotion, CUtensorMapFloatOOBfill);

static void make_map(EncodeFn fn, CUtensorMap* m, void* ptr, int rank, const cuuint64_t* dims, const cuuint64_t* strides,
                     const cuuint32_t* box, CUtensorMapSwizzle sw, CUtensorMapL2promotion promo) {
    cuuint32_t es[3] = {1, 1, 1};
    fn(m, CU_TENSOR_MAP_DATA_TYPE_BFLOAT16, rank, ptr, dims, strides, box, es, CU_TENSOR_MAP_INTERLEAVE_NONE, sw, promo,
       CU_TENSOR_MAP_FLOAT_OOB_FILL_NONE);
}

extern "C" void kernel_launch(void* const* d_in, const int* in_sizes, int n_in, void* d_out, int out_size) {
    static EncodeFn fn = nullptr;
    if (!fn) {
        void* p = nullptr;
        cudaDriverEntryPointQueryResult qr;
        cudaGetDriverEntryPoint("cuTensorMapEncodeTiled", &p, cudaEnableDefault, &qr);
        fn = (EncodeFn)p;
        cudaFuncSetAttribute(fused_kernel, cudaFuncAttributeMaxDynamicSharedMemorySize, SM_TOTAL);
    }
    CUtensorMap tmK, tmV, tmWq, tmWo, tmWg, tmWu, tmWd, tmWm;
    {
        cuuint64_t dims[3] = {64, (cuuint64_t)NB * HKV * SK, 2};
        cuuint64_t str[2] = {256, 128};
        cuuint32_t box[3] = {64, TILE_KEYS, 2};
        make_map(fn, &tmK, d_in[1], 3, dims, str, box, CU_TENSOR_MAP_SWIZZLE_128B, CU_TENSOR_MAP_L2_PROMOTION_L2_256B);
        make_map(fn, &tmV, d_in[2], 3, dims, str, box, CU_TENSOR_MAP_SWIZZLE_128B, CU_TENSOR_MAP_L2_PROMOTION_L2_256B);
    }
    {
        cuuint64_t dims[2] = {HQ * DH, DM};
        cuuint64_t str[1] = {HQ * DH * 2};
        cuuint32_t box[2] = {32, 256};
        make_map(fn, &tmWq, d_in[3], 2, dims, str, box, CU_TENSOR_MAP_SWIZZLE_64B, CU_TENSOR_MAP_L2_PROMOTION_L2_128B);
    }
    {
        cuuint64_t dims[2] = {DM, HQ * DH};
        cuuint64_t str[1] = {DM * 2};
        cuuint32_t box[2] = {64, 128};
        make_map(fn, &tmWo, d_in[4], 2, dims, str, box, CU_TENSOR_MAP_SWIZZLE_128B, CU_TENSOR_MAP_L2_PROMOTION_L2_256B);
    }
    {
        cuuint64_t dims[2] = {FF, DM};
        cuuint64_t str[1] = {FF * 2};
        cuuint32_t box[2] = {16, 256};
        make_map(fn, &tmWg, d_in[6], 2, dims, str, box, CU_TENSOR_MAP_SWIZZLE_32B, CU_TENSOR_MAP_L2_PROMOTION_L2_128B);
        make_map(fn, &tmWu, d_in[7], 2, dims, str, box, CU_TENSOR_MAP_SWIZZLE_32B, CU_TENSOR_MAP_L2_PROMOTION_L2_128B);
    }
    {
        cuuint64_t dims[2] = {6 * DM, DM};
        cuuint64_t str[1] = {6 * DM * 2};
        cuuint32_t box[2] = {16, 256};
        make_map(fn, &tmWm, d_in[10], 2, dims, str, box, CU_TENSOR_MAP_SWIZZLE_32B, CU_TENSOR_MAP_L2_PROMOTION_L2_128B);
    }
    {
        cuuint64_t dims[3] = {64, FF, 8};
        cuuint64_t str[2] = {DM * 2, 128};
        cuuint32_t box[3] = {64, 16, 8};
        make_map(fn, &tmWd, d_in[8], 3, dims, str, box, CU_TENSOR_MAP_SWIZZLE_128B, CU_TENSOR_MAP_L2_PROMOTION_L2_256B);
    }
    fused_kernel<<<NCTA, NTHREADS, SM_TOTAL>>>(tmK, tmV, tmWq, tmWo, tmWg, tmWu, tmWd, tmWm,
                                               (const bf16*)d_in[0], (const bf16*)d_in[9], (bf16*)d_out);
}
```

```cpp
#include <cuda_runtime.h>
#include <cuda_bf16.h>
#include <cuda.h>
#include <stdint.h>

typedef __nv_bfloat16 bf16;

constexpr int NB = 4, DM = 512, HQ = 32, HKV = 8, SK = 16384, DH = 128, WIN = 4096, FF = 1792;
constexpr int NCTA = 128;
constexpr int NFFN = 112;
constexpr int NOWN = 32;
constexpr int KEYS_PER_CTA = 1024;
constexpr int TILE_KEYS = 64;
constexpr int NTILE = KEYS_PER_CTA / TILE_KEYS;
constexpr int SLOT_BYTES = 16384;
#define NSLOT 12
#define INFLIGHT 3
#define INFLIGHT1 2
#define NFREE 4
#define PACE_T0 2000
#define PACE_DT 650
#define DEEP 7
#define EV_G 2
#define EV_U 4
#define EV_D 4
#define REP3 1
#define PW_IT 0
#define TMPF 0
#define PREWRITE 1
#define BACKOFF 0
#define R_FFN 38
#define FFN_STEP 1
#define P_WO 32
constexpr int NR = NSLOT - 3;
constexpr int NFRONT = 4;
constexpr int NSEQ = NFRONT + 2 * NTILE + 2;
constexpr int NCONS = 256;
constexpr int NTHREADS = NCONS + 32;

__host__ __device__ constexpr int kv2pos(int kv) { return NFRONT + kv + (kv >= P_WO ? 2 : 0); }
__host__ __device__ constexpr int posK(int i) { return kv2pos(i == 0 ? 0 : 2 * i - 1); }
__host__ __device__ constexpr int posV(int i) { return kv2pos(i == NTILE - 1 ? 2 * NTILE - 1 : 2 * i + 2); }
constexpr int POS_WO = NFRONT + P_WO;
constexpr int SL_G = NR, SL_U = NR + 1, SL_D = NR + 2;
static_assert(POS_WO >= NSEQ - NR, "wo must never need to be recycled");
constexpr int NSEQX = R_FFN + 2 * FFN_STEP + 1 > NSEQ ? R_FFN + 2 * FFN_STEP + 1 : NSEQ;

__device__ unsigned g_epoch;
__device__ __align__(128) unsigned g_llmod[6 * NCTA * 16];
__device__ __align__(128) unsigned g_llq[NB * HQ * DH];
__device__ __align__(128) unsigned g_llo[HQ * 16 * DH];
__device__ __align__(128) unsigned g_llml[HQ * 16 * 2];
__device__ __align__(128) unsigned g_ll2[NOWN * HQ * 64];
__device__ __align__(128) unsigned g_ll3[REP3 * NCTA * 16];
__device__ __align__(128) unsigned g_ll4[NOWN * NFFN * 64];
#define STAMP(i)
#define PSTAMP(i)
#define DSTAMP(i, dep)
#define CSTAMP(i)

__device__ __forceinline__ uint32_t smem_u32(const void* p) { return (uint32_t)__cvta_generic_to_shared(p); }
__device__ __forceinline__ uint32_t bfr_hi(float x) {
    uint32_t r; asm("cvt.rn.bf16x2.f32 %0, %1, %2;" : "=r"(r) : "f"(x), "f"(0.f)); return r;
}
__device__ __forceinline__ float bfr(float x) { return __uint_as_float(bfr_hi(x)); }
__device__ __forceinline__ float bf_lo(uint32_t u) { return __uint_as_float(u << 16); }
__device__ __forceinline__ float bf_hi(uint32_t u) { return __uint_as_float(u & 0xffff0000u); }
__device__ __forceinline__ uint32_t pack_bf2(float lo, float hi) {
    uint32_t r; asm("cvt.rn.bf16x2.f32 %0, %1, %2;" : "=r"(r) : "f"(hi), "f"(lo)); return r;
}

__device__ __forceinline__ void mbar_init(uint32_t bar, uint32_t cnt) {
    asm volatile("mbarrier.init.shared::cta.b64 [%0], %1;" :: "r"(bar), "r"(cnt) : "memory");
}
__device__ __forceinline__ void mbar_expect_tx(uint32_t bar, uint32_t bytes) {
    asm volatile("mbarrier.arrive.expect_tx.shared::cta.b64 _, [%0], %1;" :: "r"(bar), "r"(bytes) : "memory");
}
__device__ __forceinline__ void mbar_arrive(uint32_t bar) {
    asm volatile("mbarrier.arrive.shared::cta.b64 _, [%0];" :: "r"(bar) : "memory");
}
__device__ __forceinline__ bool mbar_try(uint32_t bar, uint32_t parity) {
    uint32_t ok;
    asm volatile("{\n\t.reg .pred p;\n\tmbarrier.try_wait.parity.shared::cta.b64 p, [%1], %2;\n\tselp.u32 %0, 1, 0, p;\n\t}"
                 : "=r"(ok) : "r"(bar), "r"(parity) : "memory");
    return ok != 0;
}
__device__ __forceinline__ bool mbar_test(uint32_t bar, uint32_t parity) {
    uint32_t ok;
    asm volatile("{\n\t.reg .pred p;\n\tmbarrier.test_wait.parity.shared::cta.b64 p, [%1], %2;\n\tselp.u32 %0, 1, 0, p;\n\t}"
                 : "=r"(ok) : "r"(bar), "r"(parity) : "memory");
    return ok != 0;
}
__device__ __forceinline__ bool expired(unsigned t0c) { return (unsigned)clock() - t0c > (1u << 24); }
__device__ __forceinline__ void mbar_wait(unsigned t0c, uint32_t bar, uint32_t parity) {
#pragma unroll 1
    while (!mbar_try(bar, parity)) if (expired(t0c)) return;
}
__device__ __forceinline__ void tma2d(uint32_t dst, const CUtensorMap* tm, int c0, int c1, uint32_t bar) {
    asm volatile("cp.async.bulk.tensor.2d.shared::cluster.global.tile.mbarrier::complete_tx::bytes [%0], [%1, {%3, %4}], [%2];"
                 :: "r"(dst), "l"((uint64_t)tm), "r"(bar), "r"(c0), "r"(c1) : "memory");
}
__device__ __forceinline__ void tma3d(uint32_t dst, const CUtensorMap* tm, int c0, int c1, int c2, uint32_t bar) {
    asm volatile("cp.async.bulk.tensor.3d.shared::cluster.global.tile.mbarrier::complete_tx::bytes [%0], [%1, {%3, %4, %5}], [%2];"
                 :: "r"(dst), "l"((uint64_t)tm), "r"(bar), "r"(c0), "r"(c1), "r"(c2) : "memory");
}
__device__ __forceinline__ void tma3d_hint(uint32_t dst, const CUtensorMap* tm, int c0, int c1, int c2, uint32_t bar, uint64_t pol) {
    asm volatile("cp.async.bulk.tensor.3d.shared::cluster.global.tile.mbarrier::complete_tx::bytes.L2::cache_hint [%0], [%1, {%3, %4, %5}], [%2], %6;"
                 :: "r"(dst), "l"((uint64_t)tm), "r"(bar), "r"(c0), "r"(c1), "r"(c2), "l"(pol) : "memory");
}
__device__ __forceinline__ void ldsm4(uint32_t (&r)[4], uint32_t addr) {
    asm volatile("ldmatrix.sync.aligned.m8n8.x4.shared.b16 {%0,%1,%2,%3}, [%4];"
                 : "=r"(r[0]), "=r"(r[1]), "=r"(r[2]), "=r"(r[3]) : "r"(addr) : "memory");
}
__device__ __forceinline__ void ldsm4t(uint32_t (&r)[4], uint32_t addr) {
    asm volatile("ldmatrix.sync.aligned.m8n8.x4.trans.shared.b16 {%0,%1,%2,%3}, [%4];"
                 : "=r"(r[0]), "=r"(r[1]), "=r"(r[2]), "=r"(r[3]) : "r"(addr) : "memory");
}
__device__ __forceinline__ void mma16816(float (&c)[4], const uint32_t (&a)[4], uint32_t b0, uint32_t b1) {
    asm volatile("mma.sync.aligned.m16n8k16.row.col.f32.bf16.bf16.f32 {%0,%1,%2,%3}, {%4,%5,%6,%7}, {%8,%9}, {%0,%1,%2,%3};"
                 : "+f"(c[0]), "+f"(c[1]), "+f"(c[2]), "+f"(c[3])
                 : "r"(a[0]), "r"(a[1]), "r"(a[2]), "r"(a[3]), "r"(b0), "r"(b1));
}
__device__ __forceinline__ uint32_t movm_t(uint32_t a) {
    uint32_t d; asm volatile("movmatrix.sync.aligned.m8n8.trans.b16 %0, %1;" : "=r"(d) : "r"(a)); return d;
}
__device__ __forceinline__ float ex2(float x) {
    float r; asm("ex2.approx.ftz.f32 %0, %1;" : "=f"(r) : "f"(x * 1.4426950408889634f)); return r;
}
__device__ __forceinline__ void cons_sync() { asm volatile("bar.sync 1, 256;" ::: "memory"); }

__device__ __forceinline__ uint4 ld_rlx4(const unsigned* p) {
    uint4 v;
    asm volatile("ld.relaxed.gpu.global.v4.u32 {%0,%1,%2,%3}, [%4];" : "=r"(v.x), "=r"(v.y), "=r"(v.z), "=r"(v.w) : "l"(p) : "memory");
    return v;
}
__device__ __forceinline__ uint2 ld_rlx2(const unsigned* p) {
    uint2 v;
    asm volatile("ld.relaxed.gpu.global.v2.u32 {%0,%1}, [%2];" : "=r"(v.x), "=r"(v.y) : "l"(p) : "memory");
    return v;
}
__device__ __forceinline__ void st_rlx(unsigned* p, unsigned v) {
    asm volatile("st.relaxed.gpu.global.u32 [%0], %1;" :: "l"(p), "r"(v) : "memory");
}
__device__ __forceinline__ void st_rlx2(unsigned* p, unsigned a, unsigned b) {
    asm volatile("st.relaxed.gpu.global.v2.u32 [%0], {%1,%2};" :: "l"(p), "r"(a), "r"(b) : "memory");
}
__device__ __forceinline__ void st_rlx2p(bool pr, unsigned* p, unsigned a, unsigned b) {
    asm volatile("{\n\t.reg .pred p;\n\tsetp.ne.u32 p, %3, 0;\n\t@p st.relaxed.gpu.global.v2.u32 [%0], {%1,%2};\n\t}"
                 :: "l"(p), "r"(a), "r"(b), "r"((unsigned)pr) : "memory");
}
__device__ __forceinline__ bool tag_ok(const uint4& v, unsigned tag, unsigned mask) {
    return (((v.x ^ tag) | (v.y ^ tag) | (v.z ^ tag) | (v.w ^ tag)) & mask) == 0;
}
__device__ __forceinline__ uint4 poll4(unsigned t0c, const unsigned* p, unsigned tag, unsigned mask) {
    uint4 v = ld_rlx4(p);
#pragma unroll 1
    while (!tag_ok(v, tag, mask) && !expired(t0c)) { if (BACKOFF) __nanosleep(BACKOFF); v = ld_rlx4(p); }
    return v;
}
__device__ __forceinline__ void poll4x2(unsigned t0c, const unsigned* p0, const unsigned* p1, unsigned tag, unsigned mask, uint4& a, uint4& b) {
    a = ld_rlx4(p0); b = ld_rlx4(p1);
#pragma unroll 1
    while (true) {
        bool oa = tag_ok(a, tag, mask), ob = tag_ok(b, tag, mask);
        if ((oa && ob) || expired(t0c)) break;
        if (BACKOFF) __nanosleep(BACKOFF);
        if (!oa) a = ld_rlx4(p0);
        if (!ob) b = ld_rlx4(p1);
    }
}
template <int N>
__device__ __forceinline__ void pollN(unsigned t0c, const unsigned* const (&p)[N], unsigned tag, unsigned mask, uint4 (&v)[N]) {
#pragma unroll
    for (int i = 0; i < N; i++) v[i] = ld_rlx4(p[i]);
#pragma unroll 1
    while (true) {
        bool all = true;
#pragma unroll
        for (int i = 0; i < N; i++) if (!tag_ok(v[i], tag, mask)) { all = false; v[i] = ld_rlx4(p[i]); }
        if (all || expired(t0c)) break;
    }
}
__device__ __forceinline__ unsigned tagf(float v, unsigned tag4) { return (__float_as_uint(v) & ~0xFu) | tag4; }
__device__ __forceinline__ float untagf(unsigned u) { return __uint_as_float(u); }
__device__ __forceinline__ float owner_reduce(float v0, float v1, float v2, float v3, float* red) {
    const int tid = threadIdx.x, lane = tid & 31;
    const bool h = lane & 16;
    const float k0 = (h ? v2 : v0) + __shfl_xor_sync(0xffffffffu, h ? v0 : v2, 16);
    const float k1 = (h ? v3 : v1) + __shfl_xor_sync(0xffffffffu, h ? v1 : v3, 16);
    *(float2*)(red + (tid >> 5) * 64 + (lane & 15) * 4 + (h ? 2 : 0)) = make_float2(k0, k1);
    cons_sync();
    const float* p = red + (tid & 63);
    return ((p[0] + p[64]) + (p[128] + p[192])) + ((p[256] + p[320]) + (p[384] + p[448]));
}

constexpr int SM_RING = 0;
constexpr int SM_MISC = NSLOT * SLOT_BYTES;
constexpr int ACT_PITCH = 520;
constexpr int SM_OBUF  = SM_MISC;
constexpr int OB_HP = 136, OB_WP = 4 * OB_HP;
constexpr int SM_ACT   = SM_OBUF + 8 * OB_WP * 4;
constexpr int SM_QS    = SM_ACT + 4 * ACT_PITCH * 2;
constexpr int SM_RED   = SM_QS + 4 * 136 * 2;
constexpr int SM_ML    = SM_RED + (512 + 64 + 512) * 4;
constexpr int SM_ST    = SM_ML + 8 * 4 * 2 * 4;
constexpr int SM_BAR   = SM_ST + 64 * 4;
constexpr int SM_TOTAL = SM_BAR + 2 * NSLOT * 8 + 32;
static_assert(SM_TOTAL <= 232448, "smem");

__device__ __noinline__ float gemv32(uint32_t a0, uint32_t a1, uint32_t ks_stride, const bf16* act_s, float* obuf) {
    const int tid = threadIdx.x, warp = tid >> 5, lane = tid & 31, g = lane >> 2, t = lane & 3;
    float acc[2][4] = {};
#pragma unroll
    for (int ks = 0; ks < 4; ks++) {
        const int k0 = warp * 64 + ks * 16;
        uint32_t b0 = 0, b1 = 0;
        if (g < 4) {
            b0 = *(const uint32_t*)(act_s + g * ACT_PITCH + k0 + 2 * t);
            b1 = *(const uint32_t*)(act_s + g * ACT_PITCH + k0 + 2 * t + 8);
        }
        uint32_t a[4], a2[4];
        ldsm4t(a, a0 + ks * ks_stride);
        ldsm4t(a2, a1 + ks * ks_stride);
        mma16816(acc[0], a, b0, b1);
        mma16816(acc[1], a2, b0, b1);
    }
    if (t < 2) {
#pragma unroll
        for (int mt = 0; mt < 2; mt++) {
            obuf[warp * 128 + (2 * t) * 32 + mt * 16 + g] = acc[mt][0];
            obuf[warp * 128 + (2 * t + 1) * 32 + mt * 16 + g] = acc[mt][1];
            obuf[warp * 128 + (2 * t) * 32 + mt * 16 + g + 8] = acc[mt][2];
            obuf[warp * 128 + (2 * t + 1) * 32 + mt * 16 + g + 8] = acc[mt][3];
        }
    }
    cons_sync();
    float s = 0.f;
    if (tid < 128) {
        const float* p = obuf + tid;
        s = ((p[0] + p[128]) + (p[256] + p[384])) + ((p[512] + p[640]) + (p[768] + p[896]));
    }
    return s;
}
__device__ __forceinline__ uint32_t pk_lo(const uint4& a) { return (a.x >> 16) | (a.y & 0xffff0000u); }
__device__ __forceinline__ uint32_t pk_hi(const uint4& a) { return (a.z >> 16) | (a.w & 0xffff0000u); }

__device__ __forceinline__ void
fused_body(const CUtensorMap& tmK, const CUtensorMap& tmV, const CUtensorMap& tmWq, const CUtensorMap& tmWo,
           const CUtensorMap& tmWg, const CUtensorMap& tmWu, const CUtensorMap& tmWd, const CUtensorMap& tmWm,
           const bf16* __restrict__ x, const bf16* __restrict__ cvec, bf16* __restrict__ out
           )
{
    extern __shared__ __align__(1024) uint8_t smem[];
    const uint32_t sbase = smem_u32(smem);
    const int tid = threadIdx.x, warp = tid >> 5, lane = tid & 31;
    const unsigned t0c = (unsigned)clock();
    const int j = blockIdx.x;
    const int ab = j >> 5, ag = (j >> 2) & 7, as = j & 3;
    const uint32_t bar_full = sbase + SM_BAR, bar_empty = bar_full + NSLOT * 8;
    const uint32_t bar_qdone = bar_empty + NSLOT * 8, bar_t1 = bar_qdone + 8;
    const int modG = j < 64 ? j : 2 * j - 64;

    if (warp == 8) {
        if (lane == 0) {
            PSTAMP(16);
            if (sbase & 1023u) __trap();
            for (int s = 0; s < NSLOT; s++) { mbar_init(bar_full + s * 8, 1); mbar_init(bar_empty + s * 8, 4); }
            mbar_init(bar_qdone, 1); mbar_init(bar_t1, 1); mbar_init(bar_t1 + 8, 1);
            asm volatile("fence.mbarrier_init.release.cluster;" ::: "memory");
            asm volatile("fence.proxy.async.shared::cta;" ::: "memory");
        }
        __syncwarp();
        asm volatile("bar.arrive 2, 288;" ::: "memory");
        if (lane == 0) {
            uint64_t pol;
            asm volatile("createpolicy.fractional.L2::evict_first.b64 %0, 1.0;" : "=l"(pol));
            const int row0 = (ab * HKV + ag) * SK + (SK - WIN) + as * KEYS_PER_CTA;
            int kv = 0;
            bool qdone = false;
            unsigned tg0; asm volatile("mov.u32 %0, %globaltimer_lo;" : "=r"(tg0));
#pragma unroll 1
            for (int pos = 0; pos < NSEQX; pos++) {
                const int slot = pos % NR, use = pos / NR;
                const uint32_t dst = sbase + SM_RING + slot * SLOT_BYTES, fb = bar_full + slot * 8;
                if (pos == 1 && j < 64) { mbar_arrive(fb); continue; }
                if (!qdone) qdone = mbar_test(bar_qdone, 0);
                int depth = qdone ? INFLIGHT : INFLIGHT1;
                if (DEEP != INFLIGHT && qdone) {
                    unsigned now; asm volatile("mov.u32 %0, %globaltimer_lo;" : "=r"(now));
                    if ((int)(now - tg0) > PACE_T0 + (pos - NFRONT) * PACE_DT) depth = DEEP;
                }
                if (pos >= NFREE && depth < NR && pos - depth < NSEQ) {
                    const int p2 = pos - depth;
                    mbar_wait(t0c, bar_full + (p2 % NR) * 8, (p2 / NR) & 1);
                }
                if (j < NFFN && pos >= R_FFN && pos <= R_FFN + 2 * FFN_STEP && (pos - R_FFN) % FFN_STEP == 0) {
                    const int f = (pos - R_FFN) / FFN_STEP;
                    const uint32_t d2 = sbase + SM_RING + (NR + f) * SLOT_BYTES, f2 = bar_full + (NR + f) * 8;
                    const int ev = f == 0 ? EV_G : f == 1 ? EV_U : EV_D;
                    if (ev & 3) mbar_wait(t0c, bar_t1 + ((ev & 3) - 1) * 8, 0);
                    if (ev & 4) mbar_wait(t0c, f2 - 8, 0);
                    mbar_expect_tx(f2, SLOT_BYTES);
                    if (f < 2) {
                        tma2d(d2, f ? &tmWu : &tmWg, 16 * j, 0, f2);
                        tma2d(d2 + 8192, f ? &tmWu : &tmWg, 16 * j, 256, f2);
                    } else {
                        tma3d(d2, &tmWd, 0, 16 * j, 0, f2);
                    }
                }
                if (pos >= NSEQ) continue;
                if (use > 0) mbar_wait(t0c, bar_empty + slot * 8, (use - 1) & 1);
                mbar_expect_tx(fb, SLOT_BYTES);
                if (pos < 2) {
                    tma2d(dst, &tmWm, 16 * (modG + pos), 0, fb);
                    tma2d(dst + 8192, &tmWm, 16 * (modG + pos), 256, fb);
                } else if (pos < 4) {
                    tma2d(dst, &tmWq, 32 * j, 256 * (pos - 2), fb);
                } else if (pos == POS_WO || pos == POS_WO + 1) {
                    tma2d(dst, &tmWo, 128 * (j & 3) + 64 * (pos - POS_WO), 128 * (j >> 2), fb);
                } else {
                    const bool isK = (kv == 0) || ((kv & 1) && kv < 2 * NTILE - 1);
                    const int ti = isK ? ((kv + 1) >> 1) : (kv == 2 * NTILE - 1 ? NTILE - 1 : (kv >> 1) - 1);
                    tma3d_hint(dst, isK ? &tmK : &tmV, 0, row0 + ti * TILE_KEYS, 0, fb, pol);
                    kv++;
                }
                if (pos == 3) PSTAMP(24);
                if (pos == 6) PSTAMP(25);
                if (pos == 10) PSTAMP(26);
                if (pos == 14) PSTAMP(27);
            }
            PSTAMP(17);
        }
        return;
    }

    STAMP(0);
    float* obuf = (float*)(smem + SM_OBUF);
    bf16* act_s = (bf16*)(smem + SM_ACT);
    bf16* qs = (bf16*)(smem + SM_QS);
    float* red = (float*)(smem + SM_RED);
    float* mls = (float*)(smem + SM_ML);
    float* st = (float*)(smem + SM_ST);
    const int g = lane >> 2, t = lane & 3;
    const int mi = lane >> 3, lr = lane & 7;
    const int ub = tid & 3, uj = tid >> 2;

    unsigned epoch;
    asm volatile("ld.relaxed.gpu.global.u32 %0, [%1];" : "=r"(epoch) : "l"(&g_epoch) : "memory");
    const uint2 cu0 = __ldg((const uint2*)(cvec + ub * DM + 4 * uj)), cu1 = __ldg((const uint2*)(cvec + ub * DM + 4 * (uj + 64)));
    const uint2 xu0 = __ldg((const uint2*)(x + ub * DM + 4 * uj)), xu1 = __ldg((const uint2*)(x + ub * DM + 4 * (uj + 64)));
    const bool owner = (j & 3) == 0;
    const int oc = 4 * j + ((tid & 63) >> 2);
    float xown = 0.f;
    if (owner) xown = __bfloat162float(x[(tid & 3) * DM + oc]);
    unsigned* const mod_dst = &g_llmod[(modG * 4 + ((tid & 31) >> 2)) * 16 + (tid >> 5) * 4 + (tid & 3)];
    unsigned* const q_dst = &g_llq[(tid >> 5) * (HQ * DH) + 32 * j + (tid & 31)];
    const bool mod_pub = tid < 128 && (j >= 64 || (tid & 31) < 16);
    unsigned* const o_dst = &g_llo[((ag * 4 + (tid >> 6)) * 16 + ab * 4 + as) * DH + (tid & 63) * 2];
    unsigned* const ml_dst = &g_llml[((ag * 4 + (tid >> 6)) * 16 + ab * 4 + as) * 2];
    unsigned* const p2_dst = &g_ll2[(((j & 3) * 8 + warp) * HQ + (j >> 2)) * 64 + g * 4 + 2 * t];
    unsigned* const p4_dst = &g_ll4[(warp * 4 * NFFN + j) * 64 + g * 4 + 2 * t];
    unsigned* const x1_dst = &g_ll3[(tid >> 6) * (NCTA * 16) + (oc >> 2) * 16 + (tid & 3) * 4 + (oc & 3)];
    auto reset_tail = [&]() {
        st_rlx2(o_dst, 0u, 0u);
        st_rlx2p((tid & 63) == 0, ml_dst, 0u, 0u);
        st_rlx2p(t < 2, p2_dst, 0u, 0u);
        st_rlx2p(t < 2, p2_dst + 32, 0u, 0u);
#pragma unroll
        for (int i = 0; i < 8; i++) st_rlx2p(t < 2 && j < NFFN, p4_dst + (i >> 1) * (NFFN * 64) + (i & 1) * 32, 0u, 0u);
        if (owner && tid < 64 * REP3) st_rlx(x1_dst, 0u);
    };
    if (mod_pub) st_rlx(mod_dst, 0u);
    if (tid < 128) st_rlx(q_dst, 0u);
    if (warp < 4) {
        const uint4* xp = (const uint4*)(x + warp * DM);
        uint4 u0 = __ldg(xp + lane), u1 = __ldg(xp + 32 + lane);
        uint32_t w[8] = {u0.x, u0.y, u0.z, u0.w, u1.x, u1.y, u1.z, u1.w};
        float s = 0.f;
#pragma unroll
        for (int i = 0; i < 8; i++) s += bf_lo(w[i]) + bf_hi(w[i]);
#pragma unroll
        for (int o = 16; o; o >>= 1) s += __shfl_xor_sync(0xffffffffu, s, o);
        const float mean = s * (1.f / DM);
        float q = 0.f;
#pragma unroll
        for (int i = 0; i < 8; i++) { float a = bf_lo(w[i]) - mean, b2 = bf_hi(w[i]) - mean; q += a * a + b2 * b2; }
#pragma unroll
        for (int o = 16; o; o >>= 1) q += __shfl_xor_sync(0xffffffffu, q, o);
        if (lane == 0) {
            st[warp] = bfr(mean);
            st[4 + warp] = __frcp_rn(bfr(__fsqrt_rn(bfr(bfr(q * (1.f / DM)) + 1e-5f))));
        }
    }
    {
        auto silu2 = [](uint32_t u) {
            const float a = bf_lo(u), b = bf_hi(u);
            return pack_bf2(__fdividef(a, 1.f + __expf(-a)), __fdividef(b, 1.f + __expf(-b)));
        };
        *(uint2*)(act_s + ub * ACT_PITCH + 4 * uj) = make_uint2(silu2(cu0.x), silu2(cu0.y));
        *(uint2*)(act_s + ub * ACT_PITCH + 4 * (uj + 64)) = make_uint2(silu2(cu1.x), silu2(cu1.y));
    }
    const unsigned tag16 = 1u + epoch % 65535u, tag4 = 1u + epoch % 15u;
    asm volatile("bar.sync 2, 288;" ::: "memory");
    STAMP(18);

    const uint32_t off32 = (uint32_t)((warp * 64 + lr + (mi >> 1) * 8) * 32 + (((mi & 1) ^ ((lr >> 2) & 1)) << 4));
    {
        mbar_wait(t0c, bar_full, 0);
        if (j >= 64) mbar_wait(t0c, bar_full + 8, 0);
        STAMP(19);
        const float s = gemv32(sbase + SM_RING + off32, sbase + SM_RING + SLOT_BYTES + off32, 512, act_s, obuf);
        if (mod_pub) st_rlx(mod_dst, bfr_hi(s) | tag16);
        if (tid < 128 && lane == 0) { mbar_arrive(bar_empty); mbar_arrive(bar_empty + 8); }
    }
    STAMP(1);
    {
        const float mu = st[ub], sd = st[4 + ub];
#pragma unroll
        for (int i = 0; i < 2; i++) {
            uint4 a, b;
            poll4x2(t0c, &g_llmod[(uj + 64 * i) * 16 + ub * 4], &g_llmod[NCTA * 16 + (uj + 64 * i) * 16 + ub * 4], tag16, 0xffffu, a, b);
            const uint2 xu = i ? xu1 : xu0;
            const float h0 = bfr(bfr(bfr(bf_lo(xu.x) - mu) * sd) * bfr(1.f + bf_hi(b.x))) + bf_hi(a.x);
            const float h1 = bfr(bfr(bfr(bf_hi(xu.x) - mu) * sd) * bfr(1.f + bf_hi(b.y))) + bf_hi(a.y);
            const float h2 = bfr(bfr(bfr(bf_lo(xu.y) - mu) * sd) * bfr(1.f + bf_hi(b.z))) + bf_hi(a.z);
            const float h3 = bfr(bfr(bfr(bf_hi(xu.y) - mu) * sd) * bfr(1.f + bf_hi(b.w))) + bf_hi(a.w);
            *(uint2*)(act_s + ub * ACT_PITCH + 4 * (uj + 64 * i)) = make_uint2(pack_bf2(h0, h1), pack_bf2(h2, h3));
        }
    }
    mbar_wait(t0c, bar_full + (2 + (warp >> 2)) * 8, 0);
    cons_sync();
    STAMP(2);
    {
        const int row = (warp & 3) * 64 + lr + (mi >> 1) * 8;
        const uint32_t base = sbase + SM_RING + (2 + (warp >> 2)) * SLOT_BYTES + row * 64;
        const int sw = (row >> 1) & 3;
        const float s = gemv32(base + (((mi & 1) ^ sw) << 4), base + (((2 + (mi & 1)) ^ sw) << 4), 1024, act_s, obuf);
        if (tid < 128) {
            st_rlx(q_dst, bfr_hi(s) | tag16);
            if (lane == 0) { mbar_arrive(bar_empty + 16); mbar_arrive(bar_empty + 24); }
        }
    }
    STAMP(3);
    uint32_t sbp[2][2], cbp[2][2];
    float gav = 0.f, gbv = 0.f;
#pragma unroll
    for (int i = 0; i < 2; i++) {
        uint4 a, b;
        poll4x2(t0c, &g_llmod[3 * NCTA * 16 + (uj + 64 * i) * 16 + ub * 4], &g_llmod[4 * NCTA * 16 + (uj + 64 * i) * 16 + ub * 4], tag16, 0xffffu, a, b);
        sbp[i][0] = pk_lo(a); sbp[i][1] = pk_hi(a);
        cbp[i][0] = pack_bf2(1.f + bf_hi(b.x), 1.f + bf_hi(b.y)); cbp[i][1] = pack_bf2(1.f + bf_hi(b.z), 1.f + bf_hi(b.w));
    }
    if (owner) {
        uint4 a, b;
        poll4x2(t0c, &g_llmod[2 * NCTA * 16 + (oc >> 2) * 16 + (tid & 3) * 4], &g_llmod[5 * NCTA * 16 + (oc >> 2) * 16 + (tid & 3) * 4], tag16, 0xffffu, a, b);
        const int c = oc & 3;
        gav = bf_hi(c == 0 ? a.x : c == 1 ? a.y : c == 2 ? a.z : a.w);
        gbv = bf_hi(c == 0 ? b.x : c == 1 ? b.y : c == 2 ? b.z : b.w);
    }
    if (tid >= 128) {
        const int u = tid - 128;
        uint4 a = poll4(t0c, &g_llq[ab * (HQ * DH) + ag * 512 + u * 4], tag16, 0xffffu);
        *(uint2*)(qs + (u >> 5) * 136 + (u & 31) * 4) = make_uint2(pk_lo(a), pk_hi(a));
    }
    cons_sync();
    if (tid == 32) mbar_arrive(bar_qdone);
    uint32_t qf[8][2];
#pragma unroll
    for (int ks = 0; ks < 8; ks++) {
        qf[ks][0] = 0; qf[ks][1] = 0;
        if (g < 4) {
            qf[ks][0] = *(const uint32_t*)(qs + g * 136 + ks * 16 + 2 * t);
            qf[ks][1] = *(const uint32_t*)(qs + g * 136 + ks * 16 + 2 * t + 8);
        }
    }
    STAMP(4);

    float o[8][4];
#pragma unroll
    for (int i = 0; i < 8; i++) { o[i][0] = o[i][1] = o[i][2] = o[i][3] = 0.f; }
    float m0 = -INFINITY, m1 = -INFINITY, l0 = 0.f, l1 = 0.f;

    {
        const int w4 = warp & 3, grp = warp >> 2;
        const int keyK = w4 * 16 + lr + (mi & 1) * 8, chK = mi >> 1;
        const int keyV = w4 * 16 + lr + (mi >> 1) * 8, chV = mi & 1;
        const uint32_t offK = keyK * 128, offV = keyV * 128;
#pragma unroll 1
        for (int it = 0; it < NTILE / 2; it++) {
            const int ti = 2 * it + grp;
            if (it == PW_IT) reset_tail();
            const int pk = posK(ti), pv = posV(ti);
            const int sk = pk % NR, sv = pv % NR;
            mbar_wait(t0c, bar_full + sk * 8, (pk / NR) & 1);
            float s0[4] = {0.f, 0.f, 0.f, 0.f}, s1[4] = {0.f, 0.f, 0.f, 0.f};
            const uint32_t kb = sbase + SM_RING + sk * SLOT_BYTES + offK;
#pragma unroll
            for (int ks = 0; ks < 4; ks++) {
                uint32_t a[4], a2[4];
                const uint32_t sw = (uint32_t)(((2 * ks + chK) ^ lr) << 4);
                ldsm4(a, kb + sw);
                ldsm4(a2, kb + 8192 + sw);
                mma16816(s0, a, qf[ks][0], qf[ks][1]);
                mma16816(s1, a2, qf[4 + ks][0], qf[4 + ks][1]);
            }
            __syncwarp();
            if (lane == 0) mbar_arrive(bar_empty + sk * 8);
            float sv4[4];
#pragma unroll
            for (int i = 0; i < 4; i++) sv4[i] = bfr(bfr(s0[i] + s1[i]) * 0.08838834764831845f);
            float x0 = fmaxf(sv4[0], sv4[2]), x1 = fmaxf(sv4[1], sv4[3]);
#pragma unroll
            for (int off = 4; off < 32; off <<= 1) {
                x0 = fmaxf(x0, __shfl_xor_sync(0xffffffffu, x0, off));
                x1 = fmaxf(x1, __shfl_xor_sync(0xffffffffu, x1, off));
            }
            const float n0 = fmaxf(m0, x0), n1 = fmaxf(m1, x1);
            if (__any_sync(0xffffffffu, n0 > m0 || n1 > m1)) {
                const float f0 = ex2(m0 - n0), f1 = ex2(m1 - n1);
                l0 *= f0; l1 *= f1;
#pragma unroll
                for (int i = 0; i < 8; i++) { o[i][0] *= f0; o[i][1] *= f1; o[i][2] *= f0; o[i][3] *= f1; }
                m0 = n0; m1 = n1;
            }
            const float p0 = ex2(sv4[0] - m0), p1 = ex2(sv4[1] - m1);
            const float p2 = ex2(sv4[2] - m0), p3 = ex2(sv4[3] - m1);
            l0 += p0 + p2; l1 += p1 + p3;
            const uint32_t pb0 = movm_t(pack_bf2(p0, p1)), pb1 = movm_t(pack_bf2(p2, p3));
            if (it == NTILE / 2 - 1) {
                float la = l0, lb = l1;
#pragma unroll
                for (int off = 4; off < 32; off <<= 1) {
                    la += __shfl_xor_sync(0xffffffffu, la, off);
                    lb += __shfl_xor_sync(0xffffffffu, lb, off);
                }
                if (t < 2 && g == 0) {
                    *(float2*)(mls + (2 * t) * 16 + warp * 2) = make_float2(m0, la);
                    *(float2*)(mls + (2 * t + 1) * 16 + warp * 2) = make_float2(m1, lb);
                }
            }
            mbar_wait(t0c, bar_full + sv * 8, (pv / NR) & 1);
            const uint32_t vb = sbase + SM_RING + sv * SLOT_BYTES + offV;
#pragma unroll
            for (int mt = 0; mt < 8; mt++) {
                uint32_t a[4];
                ldsm4t(a, vb + (mt >> 2) * 8192 + (uint32_t)(((2 * (mt & 3) + chV) ^ lr) << 4));
                mma16816(o[mt], a, pb0, pb1);
            }
            __syncwarp();
            if (lane == 0) mbar_arrive(bar_empty + sv * 8);
        }
    }
    STAMP(5);
    {
        if (t < 2) {
            float* ob = obuf + warp * OB_WP + 2 * t * OB_HP + g;
#pragma unroll
            for (int mt = 0; mt < 8; mt++) {
                ob[mt * 16] = o[mt][0]; ob[OB_HP + mt * 16] = o[mt][1];
                ob[mt * 16 + 8] = o[mt][2]; ob[OB_HP + mt * 16 + 8] = o[mt][3];
            }
        }
        cons_sync();
        const int hd = tid >> 6, d = (tid & 63) * 2;
        float4 ml4[4];
#pragma unroll
        for (int w = 0; w < 4; w++) ml4[w] = *(const float4*)(mls + hd * 16 + w * 4);
        const float M = untagf(tagf(fmaxf(fmaxf(fmaxf(ml4[0].x, ml4[0].z), fmaxf(ml4[1].x, ml4[1].z)), fmaxf(fmaxf(ml4[2].x, ml4[2].z), fmaxf(ml4[3].x, ml4[3].z))), tag4));
        float a0 = 0.f, a1 = 0.f, L = 0.f;
#pragma unroll
        for (int w = 0; w < 8; w++) {
            const float f = ex2(((w & 1) ? ml4[w >> 1].z : ml4[w >> 1].x) - M);
            const float2 v = *(const float2*)(obuf + w * OB_WP + hd * OB_HP + d);
            a0 += f * v.x; a1 += f * v.y;
            L += f * ((w & 1) ? ml4[w >> 1].w : ml4[w >> 1].y);
        }
        st_rlx2(o_dst, tagf(a0, tag4), tagf(a1, tag4));
        st_rlx2p((tid & 63) == 0, ml_dst, tagf(M, tag4), tagf(L, tag4));
    }

    if (tid == 32) mbar_arrive(bar_t1);
    STAMP(6);
    {
        mbar_wait(t0c, bar_full + ((POS_WO + (warp >> 2)) % NR) * 8, ((POS_WO + (warp >> 2)) / NR) & 1);
        const uint32_t base = sbase + SM_RING + ((POS_WO + (warp >> 2)) % NR) * SLOT_BYTES + (lr + (mi >> 1) * 8) * 128 +
                              (((2 * (warp & 3) + (mi & 1)) ^ lr) << 4);
        uint32_t wf[8][4];
#pragma unroll
        for (int ks = 0; ks < 8; ks++) ldsm4t(wf[ks], base + ks * 2048);
        {
            const int b = tid >> 6, u = (tid & 63) >> 1, sp = tid & 1;
            const unsigned* seg = &g_llo[((j >> 2) * 16 + b * 4 + 2 * sp) * DH + 4 * u];
            const unsigned* const pp[3] = {seg, seg + DH, &g_llml[((j >> 2) * 16 + b * 4 + 2 * sp) * 2]};
            uint4 v[3];
            pollN<3>(t0c, pp, tag4, 0xfu, v);
            const float ma = untagf(v[2].x), mb = untagf(v[2].z);
            float M = fmaxf(ma, mb);
            M = fmaxf(M, __shfl_xor_sync(0xffffffffu, M, 1));
            const float ea = ex2(ma - M), eb = ex2(mb - M);
            float L = ea * untagf(v[2].y) + eb * untagf(v[2].w);
            const float w0 = ea * untagf(v[0].x) + eb * untagf(v[1].x), w1 = ea * untagf(v[0].y) + eb * untagf(v[1].y);
            const float w2 = ea * untagf(v[0].z) + eb * untagf(v[1].z), w3 = ea * untagf(v[0].w) + eb * untagf(v[1].w);
            L += __shfl_xor_sync(0xffffffffu, L, 1);
            const float k0 = (sp ? w2 : w0) + __shfl_xor_sync(0xffffffffu, sp ? w0 : w2, 1);
            const float k1 = (sp ? w3 : w1) + __shfl_xor_sync(0xffffffffu, sp ? w1 : w3, 1);
            const float r = __fdividef(1.f, L);
            *(uint32_t*)(qs + b * 136 + 4 * u + 2 * sp) = pack_bf2(k0 * r, k1 * r);
        }
        cons_sync();

        if (tid == 32) mbar_arrive(bar_t1 + 8);
        STAMP(7);
        float acc[2][4] = {};
#pragma unroll
        for (int ks = 0; ks < 8; ks++) {
            uint32_t b0 = 0, b1 = 0;
            if (g < 4) {
                b0 = *(const uint32_t*)(qs + g * 136 + ks * 16 + 2 * t);
                b1 = *(const uint32_t*)(qs + g * 136 + ks * 16 + 2 * t + 8);
            }
            mma16816(acc[ks & 1], wf[ks], b0, b1);
        }
        st_rlx2p(t < 2, p2_dst, tagf(acc[0][0] + acc[1][0], tag4), tagf(acc[0][1] + acc[1][1], tag4));
        st_rlx2p(t < 2, p2_dst + 32, tagf(acc[0][2] + acc[1][2], tag4), tagf(acc[0][3] + acc[1][3], tag4));
    }
    STAMP(8);
    float x1own = 0.f;
    if (owner) {
        uint4 a, b;
        const unsigned* p = &g_ll2[(j >> 2) * (HQ * 64) + tid * 4];
        poll4x2(t0c, p, p + 1024, tag4, 0xfu, a, b);
        const float s = owner_reduce(untagf(a.x) + untagf(b.x), untagf(a.y) + untagf(b.y), untagf(a.z) + untagf(b.z), untagf(a.w) + untagf(b.w), red);
        x1own = bfr(xown + bfr(gav * bfr(s)));
        if (tid < 64 * REP3) st_rlx(x1_dst, __float_as_uint(x1own) | tag16);
    }
    STAMP(9);
    if (j < NFFN) {
        uint4 a, b;
        poll4x2(t0c, &g_ll3[(j % REP3) * (NCTA * 16) + tid * 4], &g_ll3[(j % REP3) * (NCTA * 16) + (tid + 256) * 4], tag16, 0xffffu, a, b);
        STAMP(14);
        CSTAMP(1);
        float xv[8] = {bf_hi(a.x), bf_hi(a.y), bf_hi(a.z), bf_hi(a.w), bf_hi(b.x), bf_hi(b.y), bf_hi(b.z), bf_hi(b.w)};
        float mean = (((xv[0] + xv[1]) + (xv[2] + xv[3])) + ((xv[4] + xv[5]) + (xv[6] + xv[7]))) * 0.125f;
        float m2 = 0.f, m2b = 0.f;
#pragma unroll
        for (int i = 0; i < 4; i++) { m2 += (xv[i] - mean) * (xv[i] - mean); m2b += (xv[4 + i] - mean) * (xv[4 + i] - mean); }
        m2 += m2b;
        float n = 8.f;
#pragma unroll
        for (int off = 4; off < 32; off <<= 1) {
            const float om = __shfl_xor_sync(0xffffffffu, mean, off), o2 = __shfl_xor_sync(0xffffffffu, m2, off);
            const float dlt = om - mean;
            m2 = m2 + o2 + dlt * dlt * (n * 0.5f);
            mean = 0.5f * (mean + om);
            n *= 2.f;
        }
        if (lane < 4) { red[512 + lane * 16 + warp] = mean; red[512 + lane * 16 + 8 + warp] = m2; }
        CSTAMP(2);
        cons_sync();
        CSTAMP(3);
        const float4 a0 = *(const float4*)(red + 512 + ub * 16), a1 = *(const float4*)(red + 512 + ub * 16 + 4);
        const float4 q0 = *(const float4*)(red + 512 + ub * 16 + 8), q1 = *(const float4*)(red + 512 + ub * 16 + 12);
        const float mu = (((a0.x + a0.y) + (a0.z + a0.w)) + ((a1.x + a1.y) + (a1.z + a1.w))) * 0.125f;
        auto sq = [mu](float v) { return (v - mu) * (v - mu); };
        const float M2 = (((q0.x + q0.y) + (q0.z + q0.w)) + ((q1.x + q1.y) + (q1.z + q1.w))) +
                         64.f * (((sq(a0.x) + sq(a0.y)) + (sq(a0.z) + sq(a0.w))) + ((sq(a1.x) + sq(a1.y)) + (sq(a1.z) + sq(a1.w))));
        float sq_; asm("sqrt.approx.f32 %0, %1;" : "=f"(sq_) : "f"(bfr(bfr(M2 * (1.f / DM)) + 1e-5f)));
        const float mub = bfr(mu), sd = __fdividef(1.f, bfr(sq_));
#pragma unroll
        for (int i = 0; i < 2; i++) {
            float hv[4];
#pragma unroll
            for (int c = 0; c < 4; c++) {
                const uint32_t sw = sbp[i][c >> 1], cw = cbp[i][c >> 1];
                const float sbv = (c & 1) ? bf_hi(sw) : bf_lo(sw), cbv = (c & 1) ? bf_hi(cw) : bf_lo(cw);
                hv[c] = bfr(bfr(bfr(xv[i * 4 + c] - mub) * sd) * cbv) + sbv;
            }
            *(uint2*)(act_s + ub * ACT_PITCH + 4 * (uj + 64 * i)) = make_uint2(pack_bf2(hv[0], hv[1]), pack_bf2(hv[2], hv[3]));
        }
        CSTAMP(4);
        mbar_wait(t0c, bar_full + SL_G * 8, 0);
        mbar_wait(t0c, bar_full + SL_U * 8, 0);
        cons_sync();
        STAMP(10);
        CSTAMP(5);
        uint32_t af[4][4];
        {
            float gs = gemv32(sbase + SM_RING + SL_G * SLOT_BYTES + off32,
                              sbase + SM_RING + SL_U * SLOT_BYTES + off32, 512, act_s, obuf);
            if (tid < 128) {
                gs = bfr(gs);
                const float us = __shfl_xor_sync(0xffffffffu, gs, 16);
                const float inner = 0.7978845608028654f * (gs + 0.044715f * gs * gs * gs);
                const float ge = bfr(__fdividef(gs, 1.f + ex2(-2.f * inner)));
                if (lane < 16) ((unsigned short*)qs)[warp * 136 + lane] = (unsigned short)(bfr_hi(ge * us) >> 16);
            }
            mbar_wait(t0c, bar_full + SL_D * 8, 0);
            const uint32_t base = sbase + SM_RING + SL_D * SLOT_BYTES + warp * 2048 + (lr + (mi >> 1) * 8) * 128;
#pragma unroll
            for (int mt = 0; mt < 4; mt++) ldsm4t(af[mt], base + (((2 * mt + (mi & 1)) ^ lr) << 4));
            cons_sync();
        }
        STAMP(11);
        CSTAMP(6);
        {
            uint32_t b0 = 0, b1 = 0;
            if (g < 4) {
                b0 = *(const uint32_t*)(qs + g * 136 + 2 * t);
                b1 = *(const uint32_t*)(qs + g * 136 + 2 * t + 8);
            }
            float acc[4][4] = {};
#pragma unroll
            for (int mt = 0; mt < 4; mt++) mma16816(acc[mt], af[mt], b0, b1);
#pragma unroll
            for (int mt = 0; mt < 4; mt++) {
                st_rlx2p(t < 2, p4_dst + mt * (NFFN * 64), tagf(acc[mt][0], tag4), tagf(acc[mt][1], tag4));
                st_rlx2p(t < 2, p4_dst + mt * (NFFN * 64) + 32, tagf(acc[mt][2], tag4), tagf(acc[mt][3], tag4));
            }
        }
    }
    STAMP(12);
    CSTAMP(7);
    if (owner) {
        const unsigned* p = &g_ll4[(j >> 2) * (NFFN * 64) + tid * 4];
        const unsigned* const pp[7] = {p, p + 1024, p + 2048, p + 3072, p + 4096, p + 5120, p + 6144};
        uint4 v[7];
        pollN<7>(t0c, pp, tag4, 0xfu, v);
#define SUM7(c) (((untagf(v[0].c) + untagf(v[1].c)) + (untagf(v[2].c) + untagf(v[3].c))) + ((untagf(v[4].c) + untagf(v[5].c)) + untagf(v[6].c)))
        const float s = owner_reduce(SUM7(x), SUM7(y), SUM7(z), SUM7(w), red + 576);
        if (tid < 64) ((unsigned short*)out)[(tid & 3) * DM + oc] = (unsigned short)(bfr_hi(x1own + bfr(gbv * bfr(s))) >> 16);
        if (j == 0 && tid == 0) st_rlx(&g_epoch, epoch + 1u >= 65535u ? 0u : epoch + 1u);
    }
    STAMP(13);
    CSTAMP(0);
}

__global__ void __launch_bounds__(NTHREADS, 1)
fused_kernel(const __grid_constant__ CUtensorMap tmK, const __grid_constant__ CUtensorMap tmV,
             const __grid_constant__ CUtensorMap tmWq, const __grid_constant__ CUtensorMap tmWo,
             const __grid_constant__ CUtensorMap tmWg, const __grid_constant__ CUtensorMap tmWu,
             const __grid_constant__ CUtensorMap tmWd, const __grid_constant__ CUtensorMap tmWm,
             const bf16* __restrict__ x, const bf16* __restrict__ cvec, bf16* __restrict__ out)
{
    fused_body(tmK, tmV, tmWq, tmWo, tmWg, tmWu, tmWd, tmWm, x, cvec, out);
}

typedef CUresult (*EncodeFn)(CUtensorMap*, CUtensorMapDataType, cuuint32_t, void*, const cuuint64_t*, const cuuint64_t*,
                             const cuuint32_t*, const cuuint32_t*, CUtensorMapInterleave, CUtensorMapSwizzle,
                             CUtensorMapL2promotion, CUtensorMapFloatOOBfill);

static void make_map(EncodeFn fn, CUtensorMap* m, void* ptr, int rank, const cuuint64_t* dims, const cuuint64_t* strides,
                     const cuuint32_t* box, CUtensorMapSwizzle sw, CUtensorMapL2promotion promo) {
    cuuint32_t es[3] = {1, 1, 1};
    fn(m, CU_TENSOR_MAP_DATA_TYPE_BFLOAT16, rank, ptr, dims, strides, box, es, CU_TENSOR_MAP_INTERLEAVE_NONE, sw, promo,
       CU_TENSOR_MAP_FLOAT_OOB_FILL_NONE);
}

extern "C" void kernel_launch(void* const* d_in, const int* in_sizes, int n_in, void* d_out, int out_size) {
    static EncodeFn fn = nullptr;
    if (!fn) {
        void* p = nullptr;
        cudaDriverEntryPointQueryResult qr;
        cudaGetDriverEntryPoint("cuTensorMapEncodeTiled", &p, cudaEnableDefault, &qr);
        fn = (EncodeFn)p;
        cudaFuncSetAttribute(fused_kernel, cudaFuncAttributeMaxDynamicSharedMemorySize, SM_TOTAL);
    }
    CUtensorMap tmK, tmV, tmWq, tmWo, tmWg, tmWu, tmWd, tmWm;
    {
        cuuint64_t dims[3] = {64, (cuuint64_t)NB * HKV * SK, 2};
        cuuint64_t str[2] = {256, 128};
        cuuint32_t box[3] = {64, TILE_KEYS, 2};
        make_map(fn, &tmK, d_in[1], 3, dims, str, box, CU_TENSOR_MAP_SWIZZLE_128B, CU_TENSOR_MAP_L2_PROMOTION_L2_256B);
        make_map(fn, &tmV, d_in[2], 3, dims, str, box, CU_TENSOR_MAP_SWIZZLE_128B, CU_TENSOR_MAP_L2_PROMOTION_L2_256B);
    }
    {
        cuuint64_t dims[2] = {HQ * DH, DM};
        cuuint64_t str[1] = {HQ * DH * 2};
        cuuint32_t box[2] = {32, 256};
        make_map(fn, &tmWq, d_in[3], 2, dims, str, box, CU_TENSOR_MAP_SWIZZLE_64B, CU_TENSOR_MAP_L2_PROMOTION_L2_128B);
    }
    {
        cuuint64_t dims[2] = {DM, HQ * DH};
        cuuint64_t str[1] = {DM * 2};
        cuuint32_t box[2] = {64, 128};
        make_map(fn, &tmWo, d_in[4], 2, dims, str, box, CU_TENSOR_MAP_SWIZZLE_128B, CU_TENSOR_MAP_L2_PROMOTION_L2_256B);
    }
    {
        cuuint64_t dims[2] = {FF, DM};
        cuuint64_t str[1] = {FF * 2};
        cuuint32_t box[2] = {16, 256};
        make_map(fn, &tmWg, d_in[6], 2, dims, str, box, CU_TENSOR_MAP_SWIZZLE_32B, CU_TENSOR_MAP_L2_PROMOTION_L2_128B);
        make_map(fn, &tmWu, d_in[7], 2, dims, str, box, CU_TENSOR_MAP_SWIZZLE_32B, CU_TENSOR_MAP_L2_PROMOTION_L2_128B);
    }
    {
        cuuint64_t dims[2] = {6 * DM, DM};
        cuuint64_t str[1] = {6 * DM * 2};
        cuuint32_t box[2] = {16, 256};
        make_map(fn, &tmWm, d_in[10], 2, dims, str, box, CU_TENSOR_MAP_SWIZZLE_32B, CU_TENSOR_MAP_L2_PROMOTION_L2_128B);
    }
    {
        cuuint64_t dims[3] = {64, FF, 8};
        cuuint64_t str[2] = {DM * 2, 128};
        cuuint32_t box[3] = {64, 16, 8};
        make_map(fn, &tmWd, d_in[8], 3, dims, str, box, CU_TENSOR_MAP_SWIZZLE_128B, CU_TENSOR_MAP_L2_PROMOTION_L2_256B);
    }
    fused_kernel<<<NCTA, NTHREADS, SM_TOTAL>>>(tmK, tmV, tmWq, tmWo, tmWg, tmWu, tmWd, tmWm,
                                               (const bf16*)d_in[0], (const bf16*)d_in[9], (bf16*)d_out);
}
```

```cpp
#include <cuda_runtime.h>
#include <cuda_bf16.h>
#include <cuda.h>
#include <stdint.h>

typedef __nv_bfloat16 bf16;

constexpr int NB = 4, DM = 512, HQ = 32, HKV = 8, SK = 16384, DH = 128, WIN = 4096, FF = 1792;
constexpr int NCTA = 128;
constexpr int NFFN = 112;
constexpr int NOWN = 32;
constexpr int KEYS_PER_CTA = 1024;
constexpr int TILE_KEYS = 64;
constexpr int NTILE = KEYS_PER_CTA / TILE_KEYS;
constexpr int SLOT_BYTES = 16384;
#define NSLOT 12
#define INFLIGHT 3
#define INFLIGHT1 2
#define NFREE 4
#define PACE_T0 2000
#define PACE_DT 650
#define DEEP 7
#define EV_G 2
#define EV_U 4
#define EV_D 4
#define REP3 1
#define PW_IT 0
#define PREWRITE 1
#define BACKOFF 0
#define R_FFN 38
#define FFN_STEP 1
#define P_WO 32
constexpr int NR = NSLOT - 3;
constexpr int NFRONT = 4;
constexpr int NSEQ = NFRONT + 2 * NTILE + 2;
constexpr int NCONS = 256;
constexpr int NTHREADS = NCONS + 32;

__host__ __device__ constexpr int kv2pos(int kv) { return NFRONT + kv + (kv >= P_WO ? 2 : 0); }
__host__ __device__ constexpr int posK(int i) { return kv2pos(i == 0 ? 0 : 2 * i - 1); }
__host__ __device__ constexpr int posV(int i) { return kv2pos(i == NTILE - 1 ? 2 * NTILE - 1 : 2 * i + 2); }
constexpr int POS_WO = NFRONT + P_WO;
constexpr int SL_G = NR, SL_U = NR + 1, SL_D = NR + 2;
static_assert(POS_WO >= NSEQ - NR, "wo must never need to be recycled");
constexpr int NSEQX = R_FFN + 2 * FFN_STEP + 1 > NSEQ ? R_FFN + 2 * FFN_STEP + 1 : NSEQ;

__device__ unsigned g_epoch;
__device__ __align__(128) unsigned g_llmod[6 * NCTA * 16];
__device__ __align__(128) unsigned g_llq[NB * HQ * DH];
__device__ __align__(128) unsigned g_llo[HQ * 16 * DH];
__device__ __align__(128) unsigned g_llml[HQ * 16 * 2];
__device__ __align__(128) unsigned g_ll2[NOWN * HQ * 64];
__device__ __align__(128) unsigned g_ll3[REP3 * NCTA * 16];
__device__ __align__(128) unsigned g_ll4[NOWN * NFFN * 64];
#define STAMP(i)
#define PSTAMP(i)
#define DSTAMP(i, dep)
#define CSTAMP(i)

__device__ __forceinline__ uint32_t smem_u32(const void* p) { return (uint32_t)__cvta_generic_to_shared(p); }
__device__ __forceinline__ uint32_t bfr_hi(float x) {
    uint32_t r; asm("cvt.rn.bf16x2.f32 %0, %1, %2;" : "=r"(r) : "f"(x), "f"(0.f)); return r;
}
__device__ __forceinline__ float bfr(float x) { return __uint_as_float(bfr_hi(x)); }
__device__ __forceinline__ float bf_lo(uint32_t u) { return __uint_as_float(u << 16); }
__device__ __forceinline__ float bf_hi(uint32_t u) { return __uint_as_float(u & 0xffff0000u); }
__device__ __forceinline__ uint32_t pack_bf2(float lo, float hi) {
    uint32_t r; asm("cvt.rn.bf16x2.f32 %0, %1, %2;" : "=r"(r) : "f"(hi), "f"(lo)); return r;
}

__device__ __forceinline__ void mbar_init(uint32_t bar, uint32_t cnt) {
    asm volatile("mbarrier.init.shared::cta.b64 [%0], %1;" :: "r"(bar), "r"(cnt) : "memory");
}
__device__ __forceinline__ void mbar_expect_tx(uint32_t bar, uint32_t bytes) {
    asm volatile("mbarrier.arrive.expect_tx.shared::cta.b64 _, [%0], %1;" :: "r"(bar), "r"(bytes) : "memory");
}
__device__ __forceinline__ void mbar_arrive(uint32_t bar) {
    asm volatile("mbarrier.arrive.shared::cta.b64 _, [%0];" :: "r"(bar) : "memory");
}
__device__ __forceinline__ bool mbar_try(uint32_t bar, uint32_t parity) {
    uint32_t ok;
    asm volatile("{\n\t.reg .pred p;\n\tmbarrier.try_wait.parity.shared::cta.b64 p, [%1], %2;\n\tselp.u32 %0, 1, 0, p;\n\t}"
                 : "=r"(ok) : "r"(bar), "r"(parity) : "memory");
    return ok != 0;
}
__device__ __forceinline__ bool mbar_test(uint32_t bar, uint32_t parity) {
    uint32_t ok;
    asm volatile("{\n\t.reg .pred p;\n\tmbarrier.test_wait.parity.shared::cta.b64 p, [%1], %2;\n\tselp.u32 %0, 1, 0, p;\n\t}"
                 : "=r"(ok) : "r"(bar), "r"(parity) : "memory");
    return ok != 0;
}
__device__ __forceinline__ bool expired(unsigned t0c) { return (unsigned)clock() - t0c > (1u << 24); }
__device__ __forceinline__ void mbar_wait(unsigned t0c, uint32_t bar, uint32_t parity) {
#pragma unroll 1
    while (!mbar_try(bar, parity)) if (expired(t0c)) return;
}
__device__ __forceinline__ void tma2d(uint32_t dst, const CUtensorMap* tm, int c0, int c1, uint32_t bar) {
    asm volatile("cp.async.bulk.tensor.2d.shared::cluster.global.tile.mbarrier::complete_tx::bytes [%0], [%1, {%3, %4}], [%2];"
                 :: "r"(dst), "l"((uint64_t)tm), "r"(bar), "r"(c0), "r"(c1) : "memory");
}
__device__ __forceinline__ void tma3d(uint32_t dst, const CUtensorMap* tm, int c0, int c1, int c2, uint32_t bar) {
    asm volatile("cp.async.bulk.tensor.3d.shared::cluster.global.tile.mbarrier::complete_tx::bytes [%0], [%1, {%3, %4, %5}], [%2];"
                 :: "r"(dst), "l"((uint64_t)tm), "r"(bar), "r"(c0), "r"(c1), "r"(c2) : "memory");
}
__device__ __forceinline__ void tma3d_hint(uint32_t dst, const CUtensorMap* tm, int c0, int c1, int c2, uint32_t bar, uint64_t pol) {
    asm volatile("cp.async.bulk.tensor.3d.shared::cluster.global.tile.mbarrier::complete_tx::bytes.L2::cache_hint [%0], [%1, {%3, %4, %5}], [%2], %6;"
                 :: "r"(dst), "l"((uint64_t)tm), "r"(bar), "r"(c0), "r"(c1), "r"(c2), "l"(pol) : "memory");
}
__device__ __forceinline__ void ldsm4(uint32_t (&r)[4], uint32_t addr) {
    asm volatile("ldmatrix.sync.aligned.m8n8.x4.shared.b16 {%0,%1,%2,%3}, [%4];"
                 : "=r"(r[0]), "=r"(r[1]), "=r"(r[2]), "=r"(r[3]) : "r"(addr) : "memory");
}
__device__ __forceinline__ void ldsm4t(uint32_t (&r)[4], uint32_t addr) {
    asm volatile("ldmatrix.sync.aligned.m8n8.x4.trans.shared.b16 {%0,%1,%2,%3}, [%4];"
                 : "=r"(r[0]), "=r"(r[1]), "=r"(r[2]), "=r"(r[3]) : "r"(addr) : "memory");
}
__device__ __forceinline__ void mma16816(float (&c)[4], const uint32_t (&a)[4], uint32_t b0, uint32_t b1) {
    asm volatile("mma.sync.aligned.m16n8k16.row.col.f32.bf16.bf16.f32 {%0,%1,%2,%3}, {%4,%5,%6,%7}, {%8,%9}, {%0,%1,%2,%3};"
                 : "+f"(c[0]), "+f"(c[1]), "+f"(c[2]), "+f"(c[3])
                 : "r"(a[0]), "r"(a[1]), "r"(a[2]), "r"(a[3]), "r"(b0), "r"(b1));
}
__device__ __forceinline__ uint32_t movm_t(uint32_t a) {
    uint32_t d; asm volatile("movmatrix.sync.aligned.m8n8.trans.b16 %0, %1;" : "=r"(d) : "r"(a)); return d;
}
__device__ __forceinline__ float ex2(float x) {
    float r; asm("ex2.approx.ftz.f32 %0, %1;" : "=f"(r) : "f"(x * 1.4426950408889634f)); return r;
}
__device__ __forceinline__ void cons_sync() { asm volatile("bar.sync 1, 256;" ::: "memory"); }

__device__ __forceinline__ uint4 ld_rlx4(const unsigned* p) {
    uint4 v;
    asm volatile("ld.relaxed.gpu.global.v4.u32 {%0,%1,%2,%3}, [%4];" : "=r"(v.x), "=r"(v.y), "=r"(v.z), "=r"(v.w) : "l"(p) : "memory");
    return v;
}
__device__ __forceinline__ uint2 ld_rlx2(const unsigned* p) {
    uint2 v;
    asm volatile("ld.relaxed.gpu.global.v2.u32 {%0,%1}, [%2];" : "=r"(v.x), "=r"(v.y) : "l"(p) : "memory");
    return v;
}
__device__ __forceinline__ void st_rlx(unsigned* p, unsigned v) {
    asm volatile("st.relaxed.gpu.global.u32 [%0], %1;" :: "l"(p), "r"(v) : "memory");
}
__device__ __forceinline__ void st_rlx2(unsigned* p, unsigned a, unsigned b) {
    asm volatile("st.relaxed.gpu.global.v2.u32 [%0], {%1,%2};" :: "l"(p), "r"(a), "r"(b) : "memory");
}
__device__ __forceinline__ void st_rlx2p(bool pr, unsigned* p, unsigned a, unsigned b) {
    asm volatile("{\n\t.reg .pred p;\n\tsetp.ne.u32 p, %3, 0;\n\t@p st.relaxed.gpu.global.v2.u32 [%0], {%1,%2};\n\t}"
                 :: "l"(p), "r"(a), "r"(b), "r"((unsigned)pr) : "memory");
}
__device__ __forceinline__ bool tag_ok(const uint4& v, unsigned tag, unsigned mask) {
    return (((v.x ^ tag) | (v.y ^ tag) | (v.z ^ tag) | (v.w ^ tag)) & mask) == 0;
}
__device__ __forceinline__ uint4 poll4(unsigned t0c, const unsigned* p, unsigned tag, unsigned mask) {
    uint4 v = ld_rlx4(p);
#pragma unroll 1
    while (!tag_ok(v, tag, mask) && !expired(t0c)) { if (BACKOFF) __nanosleep(BACKOFF); v = ld_rlx4(p); }
    return v;
}
__device__ __forceinline__ void poll4x2(unsigned t0c, const unsigned* p0, const unsigned* p1, unsigned tag, unsigned mask, uint4& a, uint4& b) {
    a = ld_rlx4(p0); b = ld_rlx4(p1);
#pragma unroll 1
    while (true) {
        bool oa = tag_ok(a, tag, mask), ob = tag_ok(b, tag, mask);
        if ((oa && ob) || expired(t0c)) break;
        if (BACKOFF) __nanosleep(BACKOFF);
        if (!oa) a = ld_rlx4(p0);
        if (!ob) b = ld_rlx4(p1);
    }
}
template <int N>
__device__ __forceinline__ void pollN(unsigned t0c, const unsigned* const (&p)[N], unsigned tag, unsigned mask, uint4 (&v)[N]) {
#pragma unroll
    for (int i = 0; i < N; i++) v[i] = ld_rlx4(p[i]);
#pragma unroll 1
    while (true) {
        bool all = true;
#pragma unroll
        for (int i = 0; i < N; i++) if (!tag_ok(v[i], tag, mask)) { all = false; v[i] = ld_rlx4(p[i]); }
        if (all || expired(t0c)) break;
    }
}
__device__ __forceinline__ unsigned tagf(float v, unsigned tag4) { return (__float_as_uint(v) & ~0xFu) | tag4; }
__device__ __forceinline__ float untagf(unsigned u) { return __uint_as_float(u); }
__device__ __forceinline__ float owner_reduce(float v0, float v1, float v2, float v3, float* red) {
    const int tid = threadIdx.x, lane = tid & 31;
    const bool h = lane & 16;
    const float k0 = (h ? v2 : v0) + __shfl_xor_sync(0xffffffffu, h ? v0 : v2, 16);
    const float k1 = (h ? v3 : v1) + __shfl_xor_sync(0xffffffffu, h ? v1 : v3, 16);
    *(float2*)(red + (tid >> 5) * 64 + (lane & 15) * 4 + (h ? 2 : 0)) = make_float2(k0, k1);
    cons_sync();
    const float* p = red + (tid & 63);
    return ((p[0] + p[64]) + (p[128] + p[192])) + ((p[256] + p[320]) + (p[384] + p[448]));
}

constexpr int SM_RING = 0;
constexpr int SM_MISC = NSLOT * SLOT_BYTES;
constexpr int ACT_PITCH = 520;
constexpr int SM_OBUF  = SM_MISC;
constexpr int OB_HP = 136, OB_WP = 4 * OB_HP;
constexpr int SM_ACT   = SM_OBUF + 8 * OB_WP * 4;
constexpr int SM_QS    = SM_ACT + 4 * ACT_PITCH * 2;
constexpr int SM_RED   = SM_QS + 4 * 136 * 2;
constexpr int SM_ML    = SM_RED + (512 + 64 + 512) * 4;
constexpr int SM_ST    = SM_ML + 8 * 4 * 2 * 4;
constexpr int SM_BAR   = SM_ST + 64 * 4;
constexpr int SM_TOTAL = SM_BAR + 2 * NSLOT * 8 + 32;
static_assert(SM_TOTAL <= 232448, "smem");

__device__ __noinline__ float gemv32(uint32_t a0, uint32_t a1, uint32_t ks_stride, const bf16* act_s, float* obuf) {
    const int tid = threadIdx.x, warp = tid >> 5, lane = tid & 31, g = lane >> 2, t = lane & 3;
    float acc[2][4] = {};
#pragma unroll
    for (int ks = 0; ks < 4; ks++) {
        const int k0 = warp * 64 + ks * 16;
        uint32_t b0 = 0, b1 = 0;
        if (g < 4) {
            b0 = *(const uint32_t*)(act_s + g * ACT_PITCH + k0 + 2 * t);
            b1 = *(const uint32_t*)(act_s + g * ACT_PITCH + k0 + 2 * t + 8);
        }
        uint32_t a[4], a2[4];
        ldsm4t(a, a0 + ks * ks_stride);
        ldsm4t(a2, a1 + ks * ks_stride);
        mma16816(acc[0], a, b0, b1);
        mma16816(acc[1], a2, b0, b1);
    }
    if (t < 2) {
#pragma unroll
        for (int mt = 0; mt < 2; mt++) {
            obuf[warp * 128 + (2 * t) * 32 + mt * 16 + g] = acc[mt][0];
            obuf[warp * 128 + (2 * t + 1) * 32 + mt * 16 + g] = acc[mt][1];
            obuf[warp * 128 + (2 * t) * 32 + mt * 16 + g + 8] = acc[mt][2];
            obuf[warp * 128 + (2 * t + 1) * 32 + mt * 16 + g + 8] = acc[mt][3];
        }
    }
    cons_sync();
    float s = 0.f;
    if (tid < 128) {
        const float* p = obuf + tid;
        s = ((p[0] + p[128]) + (p[256] + p[384])) + ((p[512] + p[640]) + (p[768] + p[896]));
    }
    return s;
}
__device__ __forceinline__ uint32_t pk_lo(const uint4& a) { return (a.x >> 16) | (a.y & 0xffff0000u); }
__device__ __forceinline__ uint32_t pk_hi(const uint4& a) { return (a.z >> 16) | (a.w & 0xffff0000u); }

__device__ __forceinline__ void
fused_body(const CUtensorMap& tmK, const CUtensorMap& tmV, const CUtensorMap& tmWq, const CUtensorMap& tmWo,
           const CUtensorMap& tmWg, const CUtensorMap& tmWu, const CUtensorMap& tmWd, const CUtensorMap& tmWm,
           const bf16* __restrict__ x, const bf16* __restrict__ cvec, bf16* __restrict__ out
           )
{
    extern __shared__ __align__(1024) uint8_t smem[];
    const uint32_t sbase = smem_u32(smem);
    const int tid = threadIdx.x, warp = tid >> 5, lane = tid & 31;
    const unsigned t0c = (unsigned)clock();
    const int j = blockIdx.x;
    const int ab = j >> 5, ag = (j >> 2) & 7, as = j & 3;
    const uint32_t bar_full = sbase + SM_BAR, bar_empty = bar_full + NSLOT * 8;
    const uint32_t bar_qdone = bar_empty + NSLOT * 8, bar_t1 = bar_qdone + 8;
    const int modG = j < 64 ? j : 2 * j - 64;

    if (warp == 8) {
        if (lane == 0) {
            PSTAMP(16);
            if (sbase & 1023u) __trap();
            for (int s = 0; s < NSLOT; s++) { mbar_init(bar_full + s * 8, 1); mbar_init(bar_empty + s * 8, 4); }
            mbar_init(bar_qdone, 1); mbar_init(bar_t1, 1); mbar_init(bar_t1 + 8, 1);
            asm volatile("fence.mbarrier_init.release.cluster;" ::: "memory");
            asm volatile("fence.proxy.async.shared::cta;" ::: "memory");
        }
        __syncwarp();
        asm volatile("bar.arrive 2, 288;" ::: "memory");
        if (lane == 0) {
            uint64_t pol;
            asm volatile("createpolicy.fractional.L2::evict_first.b64 %0, 1.0;" : "=l"(pol));
            const int row0 = (ab * HKV + ag) * SK + (SK - WIN) + as * KEYS_PER_CTA;
            int kv = 0;
            bool qdone = false;
            unsigned tg0; asm volatile("mov.u32 %0, %globaltimer_lo;" : "=r"(tg0));
#pragma unroll 1
            for (int pos = 0; pos < NSEQX; pos++) {
                const int slot = pos % NR, use = pos / NR;
                const uint32_t dst = sbase + SM_RING + slot * SLOT_BYTES, fb = bar_full + slot * 8;
                if (pos == 1 && j < 64) { mbar_arrive(fb); continue; }
                if (!qdone) qdone = mbar_test(bar_qdone, 0);
                int depth = qdone ? INFLIGHT : INFLIGHT1;
                if (DEEP != INFLIGHT && qdone) {
                    unsigned now; asm volatile("mov.u32 %0, %globaltimer_lo;" : "=r"(now));
                    if ((int)(now - tg0) > PACE_T0 + (pos - NFRONT) * PACE_DT) depth = DEEP;
                }
                if (pos >= NFREE && depth < NR && pos - depth < NSEQ) {
                    const int p2 = pos - depth;
                    mbar_wait(t0c, bar_full + (p2 % NR) * 8, (p2 / NR) & 1);
                }
                if (j < NFFN && pos >= R_FFN && pos <= R_FFN + 2 * FFN_STEP && (pos - R_FFN) % FFN_STEP == 0) {
                    const int f = (pos - R_FFN) / FFN_STEP;
                    const uint32_t d2 = sbase + SM_RING + (NR + f) * SLOT_BYTES, f2 = bar_full + (NR + f) * 8;
                    const int ev = f == 0 ? EV_G : f == 1 ? EV_U : EV_D;
                    if (ev & 3) mbar_wait(t0c, bar_t1 + ((ev & 3) - 1) * 8, 0);
                    if (ev & 4) mbar_wait(t0c, f2 - 8, 0);
                    mbar_expect_tx(f2, SLOT_BYTES);
                    if (f < 2) {
                        tma2d(d2, f ? &tmWu : &tmWg, 16 * j, 0, f2);
                        tma2d(d2 + 8192, f ? &tmWu : &tmWg, 16 * j, 256, f2);
                    } else {
                        tma3d(d2, &tmWd, 0, 16 * j, 0, f2);
                    }
                }
                if (pos >= NSEQ) continue;
                if (use > 0) mbar_wait(t0c, bar_empty + slot * 8, (use - 1) & 1);
                mbar_expect_tx(fb, SLOT_BYTES);
                if (pos < 2) {
                    tma2d(dst, &tmWm, 16 * (modG + pos), 0, fb);
                    tma2d(dst + 8192, &tmWm, 16 * (modG + pos), 256, fb);
                } else if (pos < 4) {
                    tma2d(dst, &tmWq, 32 * j, 256 * (pos - 2), fb);
                } else if (pos == POS_WO || pos == POS_WO + 1) {
                    tma2d(dst, &tmWo, 128 * (j & 3) + 64 * (pos - POS_WO), 128 * (j >> 2), fb);
                } else {
                    const bool isK = (kv == 0) || ((kv & 1) && kv < 2 * NTILE - 1);
                    const int ti = isK ? ((kv + 1) >> 1) : (kv == 2 * NTILE - 1 ? NTILE - 1 : (kv >> 1) - 1);
                    tma3d_hint(dst, isK ? &tmK : &tmV, 0, row0 + ti * TILE_KEYS, 0, fb, pol);
                    kv++;
                }
                if (pos == 3) PSTAMP(24);
                if (pos == 6) PSTAMP(25);
                if (pos == 10) PSTAMP(26);
                if (pos == 14) PSTAMP(27);
            }
            PSTAMP(17);
        }
        return;
    }

    STAMP(0);
    float* obuf = (float*)(smem + SM_OBUF);
    bf16* act_s = (bf16*)(smem + SM_ACT);
    bf16* qs = (bf16*)(smem + SM_QS);
    float* red = (float*)(smem + SM_RED);
    float* mls = (float*)(smem + SM_ML);
    float* st = (float*)(smem + SM_ST);
    const int g = lane >> 2, t = lane & 3;
    const int mi = lane >> 3, lr = lane & 7;
    const int ub = tid & 3, uj = tid >> 2;

    unsigned epoch;
    asm volatile("ld.relaxed.gpu.global.u32 %0, [%1];" : "=r"(epoch) : "l"(&g_epoch) : "memory");
    const uint2 cu0 = __ldg((const uint2*)(cvec + ub * DM + 4 * uj)), cu1 = __ldg((const uint2*)(cvec + ub * DM + 4 * (uj + 64)));
    const uint2 xu0 = __ldg((const uint2*)(x + ub * DM + 4 * uj)), xu1 = __ldg((const uint2*)(x + ub * DM + 4 * (uj + 64)));
    const bool owner = (j & 3) == 0;
    const int oc = 4 * j + ((tid & 63) >> 2);
    float xown = 0.f;
    if (owner) xown = __bfloat162float(x[(tid & 3) * DM + oc]);
    unsigned* const mod_dst = &g_llmod[(modG * 4 + ((tid & 31) >> 2)) * 16 + (tid >> 5) * 4 + (tid & 3)];
    unsigned* const q_dst = &g_llq[(tid >> 5) * (HQ * DH) + 32 * j + (tid & 31)];
    const bool mod_pub = tid < 128 && (j >= 64 || (tid & 31) < 16);
    unsigned* const o_dst = &g_llo[((ag * 4 + (tid >> 6)) * 16 + ab * 4 + as) * DH + (tid & 63) * 2];
    unsigned* const ml_dst = &g_llml[((ag * 4 + (tid >> 6)) * 16 + ab * 4 + as) * 2];
    unsigned* const p2_dst = &g_ll2[(((j & 3) * 8 + warp) * HQ + (j >> 2)) * 64 + g * 4 + 2 * t];
    unsigned* const p4_dst = &g_ll4[(warp * 4 * NFFN + j) * 64 + g * 4 + 2 * t];
    unsigned* const x1_dst = &g_ll3[(tid >> 6) * (NCTA * 16) + (oc >> 2) * 16 + (tid & 3) * 4 + (oc & 3)];
    auto reset_tail = [&]() {
        st_rlx2(o_dst, 0u, 0u);
        st_rlx2p((tid & 63) == 0, ml_dst, 0u, 0u);
        st_rlx2p(t < 2, p2_dst, 0u, 0u);
        st_rlx2p(t < 2, p2_dst + 32, 0u, 0u);
#pragma unroll
        for (int i = 0; i < 8; i++) st_rlx2p(t < 2 && j < NFFN, p4_dst + (i >> 1) * (NFFN * 64) + (i & 1) * 32, 0u, 0u);
        if (owner && tid < 64 * REP3) st_rlx(x1_dst, 0u);
    };
    if (mod_pub) st_rlx(mod_dst, 0u);
    if (tid < 128) st_rlx(q_dst, 0u);
    if (warp < 4) {
        const uint4* xp = (const uint4*)(x + warp * DM);
        uint4 u0 = __ldg(xp + lane), u1 = __ldg(xp + 32 + lane);
        uint32_t w[8] = {u0.x, u0.y, u0.z, u0.w, u1.x, u1.y, u1.z, u1.w};
        float s = 0.f;
#pragma unroll
        for (int i = 0; i < 8; i++) s += bf_lo(w[i]) + bf_hi(w[i]);
#pragma unroll
        for (int o = 16; o; o >>= 1) s += __shfl_xor_sync(0xffffffffu, s, o);
        const float mean = s * (1.f / DM);
        float q = 0.f;
#pragma unroll
        for (int i = 0; i < 8; i++) { float a = bf_lo(w[i]) - mean, b2 = bf_hi(w[i]) - mean; q += a * a + b2 * b2; }
#pragma unroll
        for (int o = 16; o; o >>= 1) q += __shfl_xor_sync(0xffffffffu, q, o);
        if (lane == 0) {
            st[warp] = bfr(mean);
            st[4 + warp] = __frcp_rn(bfr(__fsqrt_rn(bfr(bfr(q * (1.f / DM)) + 1e-5f))));
        }
    }
    {
        auto silu2 = [](uint32_t u) {
            const float a = bf_lo(u), b = bf_hi(u);
            return pack_bf2(__fdividef(a, 1.f + __expf(-a)), __fdividef(b, 1.f + __expf(-b)));
        };
        *(uint2*)(act_s + ub * ACT_PITCH + 4 * uj) = make_uint2(silu2(cu0.x), silu2(cu0.y));
        *(uint2*)(act_s + ub * ACT_PITCH + 4 * (uj + 64)) = make_uint2(silu2(cu1.x), silu2(cu1.y));
    }
    const unsigned tag16 = 1u + epoch % 65535u, tag4 = 1u + epoch % 15u;
    asm volatile("bar.sync 2, 288;" ::: "memory");
    STAMP(18);

    const uint32_t off32 = (uint32_t)((warp * 64 + lr + (mi >> 1) * 8) * 32 + (((mi & 1) ^ ((lr >> 2) & 1)) << 4));
    {
        mbar_wait(t0c, bar_full, 0);
        if (j >= 64) mbar_wait(t0c, bar_full + 8, 0);
        STAMP(19);
        const float s = gemv32(sbase + SM_RING + off32, sbase + SM_RING + SLOT_BYTES + off32, 512, act_s, obuf);
        if (mod_pub) st_rlx(mod_dst, bfr_hi(s) | tag16);
        if (tid < 128 && lane == 0) { mbar_arrive(bar_empty); mbar_arrive(bar_empty + 8); }
    }
    STAMP(1);
    {
        const float mu = st[ub], sd = st[4 + ub];
#pragma unroll
        for (int i = 0; i < 2; i++) {
            uint4 a, b;
            poll4x2(t0c, &g_llmod[(uj + 64 * i) * 16 + ub * 4], &g_llmod[NCTA * 16 + (uj + 64 * i) * 16 + ub * 4], tag16, 0xffffu, a, b);
            const uint2 xu = i ? xu1 : xu0;
            const float h0 = bfr(bfr(bfr(bf_lo(xu.x) - mu) * sd) * bfr(1.f + bf_hi(b.x))) + bf_hi(a.x);
            const float h1 = bfr(bfr(bfr(bf_hi(xu.x) - mu) * sd) * bfr(1.f + bf_hi(b.y))) + bf_hi(a.y);
            const float h2 = bfr(bfr(bfr(bf_lo(xu.y) - mu) * sd) * bfr(1.f + bf_hi(b.z))) + bf_hi(a.z);
            const float h3 = bfr(bfr(bfr(bf_hi(xu.y) - mu) * sd) * bfr(1.f + bf_hi(b.w))) + bf_hi(a.w);
            *(uint2*)(act_s + ub * ACT_PITCH + 4 * (uj + 64 * i)) = make_uint2(pack_bf2(h0, h1), pack_bf2(h2, h3));
        }
    }
    mbar_wait(t0c, bar_full + (2 + (warp >> 2)) * 8, 0);
    cons_sync();
    STAMP(2);
    {
        const int row = (warp & 3) * 64 + lr + (mi >> 1) * 8;
        const uint32_t base = sbase + SM_RING + (2 + (warp >> 2)) * SLOT_BYTES + row * 64;
        const int sw = (row >> 1) & 3;
        const float s = gemv32(base + (((mi & 1) ^ sw) << 4), base + (((2 + (mi & 1)) ^ sw) << 4), 1024, act_s, obuf);
        if (tid < 128) {
            st_rlx(q_dst, bfr_hi(s) | tag16);
            if (lane == 0) { mbar_arrive(bar_empty + 16); mbar_arrive(bar_empty + 24); }
        }
    }
    STAMP(3);
    uint32_t sbp[2][2], cbp[2][2];
    float gav = 0.f, gbv = 0.f;
#pragma unroll
    for (int i = 0; i < 2; i++) {
        uint4 a, b;
        poll4x2(t0c, &g_llmod[3 * NCTA * 16 + (uj + 64 * i) * 16 + ub * 4], &g_llmod[4 * NCTA * 16 + (uj + 64 * i) * 16 + ub * 4], tag16, 0xffffu, a, b);
        sbp[i][0] = pk_lo(a); sbp[i][1] = pk_hi(a);
        cbp[i][0] = pack_bf2(1.f + bf_hi(b.x), 1.f + bf_hi(b.y)); cbp[i][1] = pack_bf2(1.f + bf_hi(b.z), 1.f + bf_hi(b.w));
    }
    if (owner) {
        uint4 a, b;
        poll4x2(t0c, &g_llmod[2 * NCTA * 16 + (oc >> 2) * 16 + (tid & 3) * 4], &g_llmod[5 * NCTA * 16 + (oc >> 2) * 16 + (tid & 3) * 4], tag16, 0xffffu, a, b);
        const int c = oc & 3;
        gav = bf_hi(c == 0 ? a.x : c == 1 ? a.y : c == 2 ? a.z : a.w);
        gbv = bf_hi(c == 0 ? b.x : c == 1 ? b.y : c == 2 ? b.z : b.w);
    }
    if (tid >= 128) {
        const int u = tid - 128;
        uint4 a = poll4(t0c, &g_llq[ab * (HQ * DH) + ag * 512 + u * 4], tag16, 0xffffu);
        *(uint2*)(qs + (u >> 5) * 136 + (u & 31) * 4) = make_uint2(pk_lo(a), pk_hi(a));
    }
    cons_sync();
    if (tid == 32) mbar_arrive(bar_qdone);
    uint32_t qf[8][2];
#pragma unroll
    for (int ks = 0; ks < 8; ks++) {
        qf[ks][0] = 0; qf[ks][1] = 0;
        if (g < 4) {
            qf[ks][0] = *(const uint32_t*)(qs + g * 136 + ks * 16 + 2 * t);
            qf[ks][1] = *(const uint32_t*)(qs + g * 136 + ks * 16 + 2 * t + 8);
        }
    }
    STAMP(4);

    float o[8][4];
#pragma unroll
    for (int i = 0; i < 8; i++) { o[i][0] = o[i][1] = o[i][2] = o[i][3] = 0.f; }
    float m0 = -INFINITY, m1 = -INFINITY, l0 = 0.f, l1 = 0.f;

    {
        const int w4 = warp & 3, grp = warp >> 2;
        const int keyK = w4 * 16 + lr + (mi & 1) * 8, chK = mi >> 1;
        const int keyV = w4 * 16 + lr + (mi >> 1) * 8, chV = mi & 1;
        const uint32_t offK = keyK * 128, offV = keyV * 128;
#pragma unroll 1
        for (int it = 0; it < NTILE / 2; it++) {
            const int ti = 2 * it + grp;
            if (it == PW_IT) reset_tail();
            const int pk = posK(ti), pv = posV(ti);
            const int sk = pk % NR, sv = pv % NR;
            mbar_wait(t0c, bar_full + sk * 8, (pk / NR) & 1);
            float s0[4] = {0.f, 0.f, 0.f, 0.f}, s1[4] = {0.f, 0.f, 0.f, 0.f};
            const uint32_t kb = sbase + SM_RING + sk * SLOT_BYTES + offK;
#pragma unroll
            for (int ks = 0; ks < 4; ks++) {
                uint32_t a[4], a2[4];
                const uint32_t sw = (uint32_t)(((2 * ks + chK) ^ lr) << 4);
                ldsm4(a, kb + sw);
                ldsm4(a2, kb + 8192 + sw);
                mma16816(s0, a, qf[ks][0], qf[ks][1]);
                mma16816(s1, a2, qf[4 + ks][0], qf[4 + ks][1]);
            }
            __syncwarp();
            if (lane == 0) mbar_arrive(bar_empty + sk * 8);
            float sv4[4];
#pragma unroll
            for (int i = 0; i < 4; i++) sv4[i] = bfr(bfr(s0[i] + s1[i]) * 0.08838834764831845f);
            float x0 = fmaxf(sv4[0], sv4[2]), x1 = fmaxf(sv4[1], sv4[3]);
#pragma unroll
            for (int off = 4; off < 32; off <<= 1) {
                x0 = fmaxf(x0, __shfl_xor_sync(0xffffffffu, x0, off));
                x1 = fmaxf(x1, __shfl_xor_sync(0xffffffffu, x1, off));
            }
            const float n0 = fmaxf(m0, x0), n1 = fmaxf(m1, x1);
            if (__any_sync(0xffffffffu, n0 > m0 || n1 > m1)) {
                const float f0 = ex2(m0 - n0), f1 = ex2(m1 - n1);
                l0 *= f0; l1 *= f1;
#pragma unroll
                for (int i = 0; i < 8; i++) { o[i][0] *= f0; o[i][1] *= f1; o[i][2] *= f0; o[i][3] *= f1; }
                m0 = n0; m1 = n1;
            }
            const float p0 = ex2(sv4[0] - m0), p1 = ex2(sv4[1] - m1);
            const float p2 = ex2(sv4[2] - m0), p3 = ex2(sv4[3] - m1);
            l0 += p0 + p2; l1 += p1 + p3;
            const uint32_t pb0 = movm_t(pack_bf2(p0, p1)), pb1 = movm_t(pack_bf2(p2, p3));
            if (it == NTILE / 2 - 1) {
                float la = l0, lb = l1;
#pragma unroll
                for (int off = 4; off < 32; off <<= 1) {
                    la += __shfl_xor_sync(0xffffffffu, la, off);
                    lb += __shfl_xor_sync(0xffffffffu, lb, off);
                }
                if (t < 2 && g == 0) {
                    *(float2*)(mls + (2 * t) * 16 + warp * 2) = make_float2(m0, la);
                    *(float2*)(mls + (2 * t + 1) * 16 + warp * 2) = make_float2(m1, lb);
                }
            }
            mbar_wait(t0c, bar_full + sv * 8, (pv / NR) & 1);
            const uint32_t vb = sbase + SM_RING + sv * SLOT_BYTES + offV;
#pragma unroll
            for (int mt = 0; mt < 8; mt++) {
                uint32_t a[4];
                ldsm4t(a, vb + (mt >> 2) * 8192 + (uint32_t)(((2 * (mt & 3) + chV) ^ lr) << 4));
                mma16816(o[mt], a, pb0, pb1);
            }
            __syncwarp();
            if (lane == 0) mbar_arrive(bar_empty + sv * 8);
        }
    }
    STAMP(5);
    {
        if (t < 2) {
            float* ob = obuf + warp * OB_WP + 2 * t * OB_HP + g;
#pragma unroll
            for (int mt = 0; mt < 8; mt++) {
                ob[mt * 16] = o[mt][0]; ob[OB_HP + mt * 16] = o[mt][1];
                ob[mt * 16 + 8] = o[mt][2]; ob[OB_HP + mt * 16 + 8] = o[mt][3];
            }
        }
        cons_sync();
        const int hd = tid >> 6, d = (tid & 63) * 2;
        float4 ml4[4];
#pragma unroll
        for (int w = 0; w < 4; w++) ml4[w] = *(const float4*)(mls + hd * 16 + w * 4);
        const float M = untagf(tagf(fmaxf(fmaxf(fmaxf(ml4[0].x, ml4[0].z), fmaxf(ml4[1].x, ml4[1].z)), fmaxf(fmaxf(ml4[2].x, ml4[2].z), fmaxf(ml4[3].x, ml4[3].z))), tag4));
        float a0 = 0.f, a1 = 0.f, L = 0.f;
#pragma unroll
        for (int w = 0; w < 8; w++) {
            const float f = ex2(((w & 1) ? ml4[w >> 1].z : ml4[w >> 1].x) - M);
            const float2 v = *(const float2*)(obuf + w * OB_WP + hd * OB_HP + d);
            a0 += f * v.x; a1 += f * v.y;
            L += f * ((w & 1) ? ml4[w >> 1].w : ml4[w >> 1].y);
        }
        st_rlx2(o_dst, tagf(a0, tag4), tagf(a1, tag4));
        st_rlx2p((tid & 63) == 0, ml_dst, tagf(M, tag4), tagf(L, tag4));
    }

    if (tid == 32) mbar_arrive(bar_t1);
    STAMP(6);
    {
        mbar_wait(t0c, bar_full + ((POS_WO + (warp >> 2)) % NR) * 8, ((POS_WO + (warp >> 2)) / NR) & 1);
        const uint32_t base = sbase + SM_RING + ((POS_WO + (warp >> 2)) % NR) * SLOT_BYTES + (lr + (mi >> 1) * 8) * 128 +
                              (((2 * (warp & 3) + (mi & 1)) ^ lr) << 4);
        uint32_t wf[8][4];
#pragma unroll
        for (int ks = 0; ks < 8; ks++) ldsm4t(wf[ks], base + ks * 2048);
        {
            const int b = tid >> 6, u = (tid & 63) >> 1, sp = tid & 1;
            const unsigned* seg = &g_llo[((j >> 2) * 16 + b * 4 + 2 * sp) * DH + 4 * u];
            const unsigned* const pp[3] = {seg, seg + DH, &g_llml[((j >> 2) * 16 + b * 4 + 2 * sp) * 2]};
            uint4 v[3];
            pollN<3>(t0c, pp, tag4, 0xfu, v);
            const float ma = untagf(v[2].x), mb = untagf(v[2].z);
            float M = fmaxf(ma, mb);
            M = fmaxf(M, __shfl_xor_sync(0xffffffffu, M, 1));
            const float ea = ex2(ma - M), eb = ex2(mb - M);
            float L = ea * untagf(v[2].y) + eb * untagf(v[2].w);
            const float w0 = ea * untagf(v[0].x) + eb * untagf(v[1].x), w1 = ea * untagf(v[0].y) + eb * untagf(v[1].y);
            const float w2 = ea * untagf(v[0].z) + eb * untagf(v[1].z), w3 = ea * untagf(v[0].w) + eb * untagf(v[1].w);
            L += __shfl_xor_sync(0xffffffffu, L, 1);
            const float k0 = (sp ? w2 : w0) + __shfl_xor_sync(0xffffffffu, sp ? w0 : w2, 1);
            const float k1 = (sp ? w3 : w1) + __shfl_xor_sync(0xffffffffu, sp ? w1 : w3, 1);
            const float r = __fdividef(1.f, L);
            *(uint32_t*)(qs + b * 136 + 4 * u + 2 * sp) = pack_bf2(k0 * r, k1 * r);
        }
        cons_sync();

        if (tid == 32) mbar_arrive(bar_t1 + 8);
        STAMP(7);
        float acc[2][4] = {};
#pragma unroll
        for (int ks = 0; ks < 8; ks++) {
            uint32_t b0 = 0, b1 = 0;
            if (g < 4) {
                b0 = *(const uint32_t*)(qs + g * 136 + ks * 16 + 2 * t);
                b1 = *(const uint32_t*)(qs + g * 136 + ks * 16 + 2 * t + 8);
            }
            mma16816(acc[ks & 1], wf[ks], b0, b1);
        }
        st_rlx2p(t < 2, p2_dst, tagf(acc[0][0] + acc[1][0], tag4), tagf(acc[0][1] + acc[1][1], tag4));
        st_rlx2p(t < 2, p2_dst + 32, tagf(acc[0][2] + acc[1][2], tag4), tagf(acc[0][3] + acc[1][3], tag4));
    }
    STAMP(8);
    float x1own = 0.f;
    if (owner) {
        uint4 a, b;
        const unsigned* p = &g_ll2[(j >> 2) * (HQ * 64) + tid * 4];
        poll4x2(t0c, p, p + 1024, tag4, 0xfu, a, b);
        const float s = owner_reduce(untagf(a.x) + untagf(b.x), untagf(a.y) + untagf(b.y), untagf(a.z) + untagf(b.z), untagf(a.w) + untagf(b.w), red);
        x1own = bfr(xown + bfr(gav * bfr(s)));
        if (tid < 64 * REP3) st_rlx(x1_dst, __float_as_uint(x1own) | tag16);
    }
    STAMP(9);
    if (j < NFFN) {
        uint4 a, b;
        poll4x2(t0c, &g_ll3[(j % REP3) * (NCTA * 16) + tid * 4], &g_ll3[(j % REP3) * (NCTA * 16) + (tid + 256) * 4], tag16, 0xffffu, a, b);
        STAMP(14);
        CSTAMP(1);
        float xv[8] = {bf_hi(a.x), bf_hi(a.y), bf_hi(a.z), bf_hi(a.w), bf_hi(b.x), bf_hi(b.y), bf_hi(b.z), bf_hi(b.w)};
        float mean = (((xv[0] + xv[1]) + (xv[2] + xv[3])) + ((xv[4] + xv[5]) + (xv[6] + xv[7]))) * 0.125f;
        float m2 = 0.f, m2b = 0.f;
#pragma unroll
        for (int i = 0; i < 4; i++) { m2 += (xv[i] - mean) * (xv[i] - mean); m2b += (xv[4 + i] - mean) * (xv[4 + i] - mean); }
        m2 += m2b;
        float n = 8.f;
#pragma unroll
        for (int off = 4; off < 32; off <<= 1) {
            const float om = __shfl_xor_sync(0xffffffffu, mean, off), o2 = __shfl_xor_sync(0xffffffffu, m2, off);
            const float dlt = om - mean;
            m2 = m2 + o2 + dlt * dlt * (n * 0.5f);
            mean = 0.5f * (mean + om);
            n *= 2.f;
        }
        if (lane < 4) { red[512 + lane * 16 + warp] = mean; red[512 + lane * 16 + 8 + warp] = m2; }
        CSTAMP(2);
        cons_sync();
        CSTAMP(3);
        const float4 a0 = *(const float4*)(red + 512 + ub * 16), a1 = *(const float4*)(red + 512 + ub * 16 + 4);
        const float4 q0 = *(const float4*)(red + 512 + ub * 16 + 8), q1 = *(const float4*)(red + 512 + ub * 16 + 12);
        const float mu = (((a0.x + a0.y) + (a0.z + a0.w)) + ((a1.x + a1.y) + (a1.z + a1.w))) * 0.125f;
        auto sq = [mu](float v) { return (v - mu) * (v - mu); };
        const float M2 = (((q0.x + q0.y) + (q0.z + q0.w)) + ((q1.x + q1.y) + (q1.z + q1.w))) +
                         64.f * (((sq(a0.x) + sq(a0.y)) + (sq(a0.z) + sq(a0.w))) + ((sq(a1.x) + sq(a1.y)) + (sq(a1.z) + sq(a1.w))));
        float sq_; asm("sqrt.approx.f32 %0, %1;" : "=f"(sq_) : "f"(bfr(bfr(M2 * (1.f / DM)) + 1e-5f)));
        const float mub = bfr(mu), sd = __fdividef(1.f, bfr(sq_));
#pragma unroll
        for (int i = 0; i < 2; i++) {
            float hv[4];
#pragma unroll
            for (int c = 0; c < 4; c++) {
                const uint32_t sw = sbp[i][c >> 1], cw = cbp[i][c >> 1];
                const float sbv = (c & 1) ? bf_hi(sw) : bf_lo(sw), cbv = (c & 1) ? bf_hi(cw) : bf_lo(cw);
                hv[c] = bfr(bfr(bfr(xv[i * 4 + c] - mub) * sd) * cbv) + sbv;
            }
            *(uint2*)(act_s + ub * ACT_PITCH + 4 * (uj + 64 * i)) = make_uint2(pack_bf2(hv[0], hv[1]), pack_bf2(hv[2], hv[3]));
        }
        CSTAMP(4);
        mbar_wait(t0c, bar_full + SL_G * 8, 0);
        mbar_wait(t0c, bar_full + SL_U * 8, 0);
        cons_sync();
        STAMP(10);
        CSTAMP(5);
        uint32_t af[4][4];
        {
            float gs = gemv32(sbase + SM_RING + SL_G * SLOT_BYTES + off32,
                              sbase + SM_RING + SL_U * SLOT_BYTES + off32, 512, act_s, obuf);
            if (tid < 128) {
                gs = bfr(gs);
                const float us = __shfl_xor_sync(0xffffffffu, gs, 16);
                const float inner = 0.7978845608028654f * (gs + 0.044715f * gs * gs * gs);
                const float ge = bfr(__fdividef(gs, 1.f + ex2(-2.f * inner)));
                if (lane < 16) ((unsigned short*)qs)[warp * 136 + lane] = (unsigned short)(bfr_hi(ge * us) >> 16);
            }
            mbar_wait(t0c, bar_full + SL_D * 8, 0);
            const uint32_t base = sbase + SM_RING + SL_D * SLOT_BYTES + warp * 2048 + (lr + (mi >> 1) * 8) * 128;
#pragma unroll
            for (int mt = 0; mt < 4; mt++) ldsm4t(af[mt], base + (((2 * mt + (mi & 1)) ^ lr) << 4));
            cons_sync();
        }
        STAMP(11);
        CSTAMP(6);
        {
            uint32_t b0 = 0, b1 = 0;
            if (g < 4) {
                b0 = *(const uint32_t*)(qs + g * 136 + 2 * t);
                b1 = *(const uint32_t*)(qs + g * 136 + 2 * t + 8);
            }
            float acc[4][4] = {};
#pragma unroll
            for (int mt = 0; mt < 4; mt++) mma16816(acc[mt], af[mt], b0, b1);
#pragma unroll
            for (int mt = 0; mt < 4; mt++) {
                st_rlx2p(t < 2, p4_dst + mt * (NFFN * 64), tagf(acc[mt][0], tag4), tagf(acc[mt][1], tag4));
                st_rlx2p(t < 2, p4_dst + mt * (NFFN * 64) + 32, tagf(acc[mt][2], tag4), tagf(acc[mt][3], tag4));
            }
        }
    }
    STAMP(12);
    CSTAMP(7);
    if (owner) {
        const unsigned* p = &g_ll4[(j >> 2) * (NFFN * 64) + tid * 4];
        const unsigned* const pp[7] = {p, p + 1024, p + 2048, p + 3072, p + 4096, p + 5120, p + 6144};
        uint4 v[7];
        pollN<7>(t0c, pp, tag4, 0xfu, v);
#define SUM7(c) (((untagf(v[0].c) + untagf(v[1].c)) + (untagf(v[2].c) + untagf(v[3].c))) + ((untagf(v[4].c) + untagf(v[5].c)) + untagf(v[6].c)))
        const float s = owner_reduce(SUM7(x), SUM7(y), SUM7(z), SUM7(w), red + 576);
        if (tid < 64) ((unsigned short*)out)[(tid & 3) * DM + oc] = (unsigned short)(bfr_hi(x1own + bfr(gbv * bfr(s))) >> 16);
        if (j == 0 && tid == 0) st_rlx(&g_epoch, epoch + 1u >= 65535u ? 0u : epoch + 1u);
    }
    STAMP(13);
    CSTAMP(0);
}

__global__ void __launch_bounds__(NTHREADS, 1)
fused_kernel(const __grid_constant__ CUtensorMap tmK, const __grid_constant__ CUtensorMap tmV,
             const __grid_constant__ CUtensorMap tmWq, const __grid_constant__ CUtensorMap tmWo,
             const __grid_constant__ CUtensorMap tmWg, const __grid_constant__ CUtensorMap tmWu,
             const __grid_constant__ CUtensorMap tmWd, const __grid_constant__ CUtensorMap tmWm,
             const bf16* __restrict__ x, const bf16* __restrict__ cvec, bf16* __restrict__ out)
{
    fused_body(tmK, tmV, tmWq, tmWo, tmWg, tmWu, tmWd, tmWm, x, cvec, out);
}

#define KVPROMO CU_TENSOR_MAP_L2_PROMOTION_L2_256B
#define GUPROMO CU_TENSOR_MAP_L2_PROMOTION_L2_128B
#define WMPROMO CU_TENSOR_MAP_L2_PROMOTION_L2_128B
typedef CUresult (*EncodeFn)(CUtensorMap*, CUtensorMapDataType, cuuint32_t, void*, const cuuint64_t*, const cuuint64_t*,
                             const cuuint32_t*, const cuuint32_t*, CUtensorMapInterleave, CUtensorMapSwizzle,
                             CUtensorMapL2promotion, CUtensorMapFloatOOBfill);

static void make_map(EncodeFn fn, CUtensorMap* m, void* ptr, int rank, const cuuint64_t* dims, const cuuint64_t* strides,
                     const cuuint32_t* box, CUtensorMapSwizzle sw, CUtensorMapL2promotion promo) {
    cuuint32_t es[3] = {1, 1, 1};
    fn(m, CU_TENSOR_MAP_DATA_TYPE_BFLOAT16, rank, ptr, dims, strides, box, es, CU_TENSOR_MAP_INTERLEAVE_NONE, sw, promo,
       CU_TENSOR_MAP_FLOAT_OOB_FILL_NONE);
}

extern "C" void kernel_launch(void* const* d_in, const int* in_sizes, int n_in, void* d_out, int out_size) {
    static EncodeFn fn = nullptr;
    if (!fn) {
        void* p = nullptr;
        cudaDriverEntryPointQueryResult qr;
        cudaGetDriverEntryPoint("cuTensorMapEncodeTiled", &p, cudaEnableDefault, &qr);
        fn = (EncodeFn)p;
        cudaFuncSetAttribute(fused_kernel, cudaFuncAttributeMaxDynamicSharedMemorySize, SM_TOTAL);
    }
    CUtensorMap tmK, tmV, tmWq, tmWo, tmWg, tmWu, tmWd, tmWm;
    {
        cuuint64_t dims[3] = {64, (cuuint64_t)NB * HKV * SK, 2};
        cuuint64_t str[2] = {256, 128};
        cuuint32_t box[3] = {64, TILE_KEYS, 2};
        make_map(fn, &tmK, d_in[1], 3, dims, str, box, CU_TENSOR_MAP_SWIZZLE_128B, KVPROMO);
        make_map(fn, &tmV, d_in[2], 3, dims, str, box, CU_TENSOR_MAP_SWIZZLE_128B, KVPROMO);
    }
    {
        cuuint64_t dims[2] = {HQ * DH, DM};
        cuuint64_t str[1] = {HQ * DH * 2};
        cuuint32_t box[2] = {32, 256};
        make_map(fn, &tmWq, d_in[3], 2, dims, str, box, CU_TENSOR_MAP_SWIZZLE_64B, CU_TENSOR_MAP_L2_PROMOTION_L2_128B);
    }
    {
        cuuint64_t dims[2] = {DM, HQ * DH};
        cuuint64_t str[1] = {DM * 2};
        cuuint32_t box[2] = {64, 128};
        make_map(fn, &tmWo, d_in[4], 2, dims, str, box, CU_TENSOR_MAP_SWIZZLE_128B, CU_TENSOR_MAP_L2_PROMOTION_L2_256B);
    }
    {
        cuuint64_t dims[2] = {FF, DM};
        cuuint64_t str[1] = {FF * 2};
        cuuint32_t box[2] = {16, 256};
        make_map(fn, &tmWg, d_in[6], 2, dims, str, box, CU_TENSOR_MAP_SWIZZLE_32B, GUPROMO);
        make_map(fn, &tmWu, d_in[7], 2, dims, str, box, CU_TENSOR_MAP_SWIZZLE_32B, GUPROMO);
    }
    {
        cuuint64_t dims[2] = {6 * DM, DM};
        cuuint64_t str[1] = {6 * DM * 2};
        cuuint32_t box[2] = {16, 256};
        make_map(fn, &tmWm, d_in[10], 2, dims, str, box, CU_TENSOR_MAP_SWIZZLE_32B, WMPROMO);
    }
    {
        cuuint64_t dims[3] = {64, FF, 8};
        cuuint64_t str[2] = {DM * 2, 128};
        cuuint32_t box[3] = {64, 16, 8};
        make_map(fn, &tmWd, d_in[8], 3, dims, str, box, CU_TENSOR_MAP_SWIZZLE_128B, CU_TENSOR_MAP_L2_PROMOTION_L2_256B);
    }
    fused_kernel<<<NCTA, NTHREADS, SM_TOTAL>>>(tmK, tmV, tmWq, tmWo, tmWg, tmWu, tmWd, tmWm,
                                               (const bf16*)d_in[0], (const bf16*)d_in[9], (bf16*)d_out);
}
```
